```python
import torch

def _softmax(x, axis=-1):
    return torch.softmax(x, dim=axis)
def _gelu(x):
    return torch.nn.functional.gelu(x, approximate="tanh")
def _silu(x):
    return torch.nn.functional.silu(x)
def _sigmoid(x):
    return torch.sigmoid(x)
def _layernorm(x, axis=-1, eps=1e-5):
    m = x.mean(dim=axis, keepdim=True)
    v = x.var(dim=axis, keepdim=True, unbiased=False)
    return (x - m) / torch.sqrt(v + eps)
def _scatter_add(tgt, idx, src, axis=0):
    return tgt.clone().index_add_(axis, idx, src)
def _segment_sum(src, seg, n):
    out = torch.zeros((n,) + src.shape[1:], dtype=src.dtype)
    return out.index_add_(0, seg, src)
def _pad(x, pw):
    flat = tuple(v for pair in reversed(pw) for v in pair)
    return torch.nn.functional.pad(x, flat)

kernel_name = 'recurrent_scan__ssm_conv_s5__dense_activation_relu__prompt'

def setup_inputs():

    _w = (lambda a: (lambda t: t.to(torch.bfloat16) if t.is_floating_point() else t)(torch.as_tensor(a)))
    def _A_setup():
        B, S, D = 1, 2048, 640
        P = D
        Lambda_re = -0.5 * (lambda _x: torch.exp(torch.as_tensor(_x)))((lambda *s: torch.randn(*s, dtype=torch.bfloat16) * 0.2)(P))
        Lambda_im = (lambda *s: torch.randn(*s, dtype=torch.bfloat16) * 0.4)(P) * 1.0
        B_re = (lambda *s: torch.randn(*s, dtype=torch.bfloat16) * 0.2)(P, D) * (D ** -0.5)
        B_im = (lambda *s: torch.randn(*s, dtype=torch.bfloat16) * 0.2)(P, D) * (D ** -0.5)
        C_re = (lambda *s: torch.randn(*s, dtype=torch.bfloat16) * 0.2)(D, P) * (P ** -0.5)
        C_im = (lambda *s: torch.randn(*s, dtype=torch.bfloat16) * 0.2)(D, P) * (P ** -0.5)
        log_dt = (lambda *s: torch.randn(*s, dtype=torch.bfloat16) * 0.2)(P) * 0.3 - 2.0
        Dskip = (lambda *s: torch.randn(*s, dtype=torch.bfloat16) * 0.05)(D)
        return {
            "x": _w((lambda *s: torch.randn(*s, dtype=torch.bfloat16) * 0.05)(B, S, D)),
            "Lambda_re": _w(Lambda_re),
            "Lambda_im": _w(Lambda_im),
            "B_re": _w(B_re),
            "B_im": _w(B_im),
            "C_re": _w(C_re),
            "C_im": _w(C_im),
            "log_dt": _w(log_dt),
            "Dskip": _w(Dskip),
        }
    _A_in = _A_setup()

    def _B_setup():
        B, S, D, Dff = 1, 2048, 640, 1536
        return {
            "x": _w((lambda *s: torch.randn(*s, dtype=torch.bfloat16) * 0.05)(B, S, D)),
            "w1": _w((lambda *s: torch.randn(*s, dtype=torch.bfloat16) * 0.05)(D, Dff)),
            "w2": _w((lambda *s: torch.randn(*s, dtype=torch.bfloat16) * 0.05)(Dff, D)),
        }
    _B_in = _B_setup()

    return {
        "A_x": _A_in["x"],
        "A_Lambda_re": _A_in["Lambda_re"],
        "A_Lambda_im": _A_in["Lambda_im"],
        "A_B_re": _A_in["B_re"],
        "A_B_im": _A_in["B_im"],
        "A_C_re": _A_in["C_re"],
        "A_C_im": _A_in["C_im"],
        "A_log_dt": _A_in["log_dt"],
        "A_Dskip": _A_in["Dskip"],
        "B_x": _B_in["x"],
        "B_w1": _B_in["w1"],
        "B_w2": _B_in["w2"],
    }

def reference(A_x, A_Lambda_re, A_Lambda_im, A_B_re, A_B_im, A_C_re, A_C_im, A_log_dt, A_Dskip, B_x, B_w1, B_w2):
    def _A_ref(x, Lambda_re, Lambda_im, B_re, B_im, C_re, C_im, log_dt, Dskip):
        Bsz, L, H = x.shape
        Lam = Lambda_re + 1j * Lambda_im
        Bmat = B_re + 1j * B_im
        Cmat = C_re + 1j * C_im
        dt = torch.exp(log_dt)
        Lam_bar = torch.exp(dt * Lam)
        B_bar = ((Lam_bar - 1.0) / Lam)[:, None] * Bmat
        Bu = torch.einsum("bld,pd->blp", x + 0j, B_bar)
        h = torch.zeros_like(Bu[:, 0, :])
        hs = []
        for t in range(L):
            h = Lam_bar[None, :] * h + Bu[:, t, :]
            hs.append(h)
        hseq = torch.stack(hs, 1)
        y = 2.0 * torch.einsum("blp,dp->bld", hseq, Cmat).real + x * Dskip[None, None, :]
        return y

    def _B_ref(x, w1, w2):
        h = torch.einsum("bsd,df->bsf", x, w1)
        zero = torch.zeros_like(h)
        h = torch.maximum(h, zero)
        return torch.einsum("bsf,fd->bsd", h, w2)

    x = A_x
    xn = _layernorm(x, axis=-1)
    s = _A_ref(xn, A_Lambda_re, A_Lambda_im, A_B_re, A_B_im, A_C_re, A_C_im, A_log_dt, A_Dskip)
    g = _silu(_B_ref(xn, B_w1, B_w2))
    return x + s * g
```

```cpp
#include <cuda_runtime.h>
#include <cuda_bf16.h>
#include <cuda.h>
#include <stdint.h>

namespace {

constexpr int SEQ = 2048, DM = 640, FF = 1536;
constexpr int NCH = 16;
constexpr uint32_t XKB = 16384;
constexpr uint32_t W_OFF = 10 * XKB;
constexpr uint32_t WSLOT = 16384;
constexpr int      NW = 4;
constexpr uint32_t ST2 = 36864;
constexpr int      NS2 = 6;
constexpr uint32_t MISC = W_OFF + NW * WSLOT;
constexpr uint32_t B_XFULL = MISC, B_WFULL = MISC + 80, B_FULL2 = MISC + 112, B_EPOCH = MISC + 160, B_P2GO = MISC + 168,
                   B_WEMPTY = MISC + 176,
                   B_EMPTY2 = MISC + 208,
                   B_STATS = MISC + 256,
                   B_RX = MISC + 264,
                   B_TAILGO = MISC + 280, B_XT = MISC + 288,
                   EPOCH_VAL = MISC + 296, RDY_MASK = MISC + 300;
constexpr uint32_t STAT_R = MISC + 384;
constexpr uint32_t STAT_M = MISC + 1024;
constexpr uint32_t SMEM_BYTES = STAT_M + 2048;
#define DT 3
constexpr int DTAIL = DT;
constexpr int NB_TURN0 = 1, NB_WG0 = 5, NB_MEAN0 = 9, NB_TAIL0 = 12;
constexpr int NTHREADS = 512;
#define ABL 0
#define PF_NS 500
#define POLL_NS 0
#define PF_MODE 0
#define PACED 0
#define PACE_NS 0
#define PF_AT 2

struct Params {
  CUtensorMap mx, mb[2], mw1, mc[2], mw2, mp[3], mo, mx2;
  const __nv_bfloat16 *x, *lam_re, *lam_im, *log_dt, *dskip, *b_re, *b_im, *c_re, *c_im, *w1, *w2;
  float* out;
  int use_smid, nblocks;
};

__device__ __align__(1024) uint4 g_act[NCH][44][1024];
__device__ __align__(128) uint32_t g_flags[NCH][64];
__device__ __align__(128) uint2 g_agg[80][NCH][8];
__device__ __align__(128) uint4 g_xg[NCH][4][4][256];
__device__ __align__(128) uint4 g_xy[NCH][4][6][256];
__device__ __align__(128) uint2 g_stat[SEQ];
__device__ __align__(128) uint32_t g_cs[FF + 2 * DM];
__device__ __align__(128) uint4 g_lam[DM];
__device__ uint32_t g_epoch;
__device__ uint32_t g_started;
#define TS(i)
#define TS2(u, k)

__device__ __forceinline__ uint32_t smem_u32(const void* p) { return (uint32_t)__cvta_generic_to_shared(p); }
__device__ __forceinline__ bool elect_one() {
  uint32_t p;
  asm volatile("{\n.reg .pred P;\nelect.sync _|P, 0xffffffff;\nselp.u32 %0, 1, 0, P;\n}" : "=r"(p));
  return p;
}
__device__ __forceinline__ void mbar_init(uint32_t bar, uint32_t cnt) { asm volatile("mbarrier.init.shared::cta.b64 [%0], %1;" ::"r"(bar), "r"(cnt)); }
__device__ __forceinline__ void mbar_expect_tx(uint32_t bar, uint32_t bytes) {
  asm volatile("mbarrier.arrive.expect_tx.shared::cta.b64 _, [%0], %1;" ::"r"(bar), "r"(bytes) : "memory");
}
__device__ __forceinline__ void mbar_arrive(uint32_t bar) { asm volatile("mbarrier.arrive.shared::cta.b64 _, [%0];" ::"r"(bar) : "memory"); }
__device__ __forceinline__ void mbar_arrive_both(uint32_t bar, uint32_t lane) {
  asm volatile("{\n.reg .pred p;\n.reg .b32 r;\nsetp.lt.u32 p, %1, 2;\nmapa.shared::cluster.u32 r, %0, %2;\n"
               "@p mbarrier.arrive.shared::cluster.b64 _, [r];\n}" ::"r"(bar), "r"(lane), "r"(lane & 1) : "memory");
}
__device__ __forceinline__ uint32_t mapa(uint32_t addr, uint32_t cta) { uint32_t r; asm("mapa.shared::cluster.u32 %0, %1, %2;" : "=r"(r) : "r"(addr), "r"(cta)); return r; }
__device__ __forceinline__ void mbar_arrive_if(uint32_t cluster_addr, uint32_t cond) {
  asm volatile("{\n.reg .pred p;\nsetp.ne.u32 p, %1, 0;\n@p mbarrier.arrive.shared::cluster.b64 _, [%0];\n}" ::"r"(cluster_addr), "r"(cond) : "memory");
}
__device__ __forceinline__ void mbar_wait(uint32_t bar, uint32_t parity) {
  asm volatile("{\n.reg .pred p;\n.reg .u32 n;\n"
               "mbarrier.try_wait.parity.shared::cta.b64 p, [%0], %1;\n@p bra LAB_DONE;\nmov.u32 n, 0;\n"
               "LAB_WAIT:\nmbarrier.try_wait.parity.shared::cta.b64 p, [%0], %1;\n@p bra LAB_DONE;\n"
               "add.u32 n, n, 1;\nsetp.lt.u32 p, n, 0x4000;\n@p bra LAB_WAIT;\nLAB_DONE:\n}" ::"r"(bar), "r"(parity) : "memory");
}
__device__ __forceinline__ bool mbar_test(uint32_t bar, uint32_t parity) {
  uint32_t ok;
  asm volatile("{\n.reg .pred p;\nmbarrier.test_wait.parity.shared::cta.b64 p, [%1], %2;\nselp.u32 %0, 1, 0, p;\n}" : "=r"(ok) : "r"(bar), "r"(parity) : "memory");
  return __shfl_sync(0xffffffffu, ok, 0);
}
__device__ __forceinline__ void nb_sync(int id, int n) { asm volatile("bar.sync %0, %1;" ::"r"(id), "r"(n) : "memory"); }
__device__ __forceinline__ void nb_arrive(int id, int n) { asm volatile("bar.arrive %0, %1;" ::"r"(id), "r"(n) : "memory"); }
__device__ __forceinline__ void tma_2d_mc(uint32_t dst, const CUtensorMap* m, int c0, int c1, uint32_t bar) {
  asm volatile("cp.async.bulk.tensor.2d.shared::cluster.global.mbarrier::complete_tx::bytes.multicast::cluster [%0], [%1, {%3, %4}], [%2], %5;"
               ::"r"(dst), "l"(m), "r"(bar), "r"(c0), "r"(c1), "h"((uint16_t)3) : "memory");
}
__device__ __forceinline__ void tma_2d(uint32_t dst, const CUtensorMap* m, int c0, int c1, uint32_t bar) {
  asm volatile("cp.async.bulk.tensor.2d.shared::cluster.global.mbarrier::complete_tx::bytes [%0], [%1, {%3, %4}], [%2];"
               ::"r"(dst), "l"(m), "r"(bar), "r"(c0), "r"(c1) : "memory");
}
__device__ __forceinline__ void tma_3d_mc(uint32_t dst, const CUtensorMap* m, int c0, int c1, int c2, uint32_t bar) {
  asm volatile("cp.async.bulk.tensor.3d.shared::cluster.global.mbarrier::complete_tx::bytes.multicast::cluster [%0], [%1, {%3, %4, %5}], [%2], %6;"
               ::"r"(dst), "l"(m), "r"(bar), "r"(c0), "r"(c1), "r"(c2), "h"((uint16_t)3) : "memory");
}
__device__ __forceinline__ void tma_3d(uint32_t dst, const CUtensorMap* m, int c0, int c1, int c2, uint32_t bar) {
  asm volatile("cp.async.bulk.tensor.3d.shared::cluster.global.mbarrier::complete_tx::bytes [%0], [%1, {%3, %4, %5}], [%2];"
               ::"r"(dst), "l"(m), "r"(bar), "r"(c0), "r"(c1), "r"(c2) : "memory");
}
__device__ __forceinline__ void bulk_load(uint32_t dst, const void* src, uint32_t bytes, uint32_t bar) {
  asm volatile("cp.async.bulk.shared::cluster.global.mbarrier::complete_tx::bytes [%0], [%1], %2, [%3];"
               ::"r"(dst), "l"(src), "r"(bytes), "r"(bar) : "memory");
}
__device__ __forceinline__ void l2_prefetch(const void* base, int lines, int lane) {
#pragma unroll 1
  for (int i = lane; i < lines; i += 32) asm volatile("prefetch.global.L2 [%0];" ::"l"(reinterpret_cast<const char*>(base) + i * 128) : "memory");
}
__device__ __forceinline__ void prefetch_map(const CUtensorMap* m) { asm volatile("prefetch.tensormap [%0];" ::"l"(m) : "memory"); }
__device__ __forceinline__ void wg_fence() { asm volatile("wgmma.fence.sync.aligned;" ::: "memory"); }
__device__ __forceinline__ void wg_commit() { asm volatile("wgmma.commit_group.sync.aligned;" ::: "memory"); }
template <int N> __device__ __forceinline__ void wg_wait() { asm volatile("wgmma.wait_group.sync.aligned %0;" ::"n"(N) : "memory"); }
template <int N> __device__ __forceinline__ void fence_regs(float (&d)[N]) {
#pragma unroll
  for (int i = 0; i < N; i++) asm volatile("" : "+f"(d[i])::"memory");
}
template <int LO, int HI, int N> __device__ __forceinline__ void fence_regs_range(float (&d)[N]) {
#pragma unroll
  for (int i = LO; i < HI; i++) asm volatile("" : "+f"(d[i])::"memory");
}
constexpr uint32_t SB_LO = 1024;
__host__ __device__ constexpr uint32_t dlo(uint32_t off, uint32_t lbo) { return ((SB_LO + off) >> 4) | ((lbo >> 4) << 16); }
__host__ __device__ constexpr uint32_t dhi(uint32_t sbo, uint32_t swz) { return (sbo >> 4) | (swz << 30); }
__device__ __forceinline__ float4 lds128f(uint32_t a) {
  float4 v; asm volatile("ld.shared.v4.f32 {%0,%1,%2,%3}, [%4];" : "=f"(v.x), "=f"(v.y), "=f"(v.z), "=f"(v.w) : "r"(a)); return v;
}
__device__ __forceinline__ uint4 lds128u(uint32_t a) {
  uint4 v; asm volatile("ld.shared.v4.u32 {%0,%1,%2,%3}, [%4];" : "=r"(v.x), "=r"(v.y), "=r"(v.z), "=r"(v.w) : "r"(a) : "memory"); return v;
}
__device__ __forceinline__ float lds32f(uint32_t a) { float v; asm volatile("ld.shared.f32 %0, [%1];" : "=f"(v) : "r"(a)); return v; }
__device__ __forceinline__ uint32_t lds32u(uint32_t a) { uint32_t v; asm volatile("ld.shared.u32 %0, [%1];" : "=r"(v) : "r"(a) : "memory"); return v; }
__device__ __forceinline__ uint32_t lds_acquire(uint32_t a) { uint32_t v; asm volatile("ld.acquire.cta.shared.u32 %0, [%1];" : "=r"(v) : "r"(a) : "memory"); return v; }
__device__ __forceinline__ void sts32f(uint32_t a, float v) { asm volatile("st.shared.f32 [%0], %1;" ::"r"(a), "f"(v) : "memory"); }
__device__ __forceinline__ void sts32u(uint32_t a, uint32_t v) { asm volatile("st.shared.u32 [%0], %1;" ::"r"(a), "r"(v) : "memory"); }
__device__ __forceinline__ float bf_lo(uint32_t w) { return __uint_as_float(w << 16); }
__device__ __forceinline__ float bf_hi(uint32_t w) { return __uint_as_float(w & 0xffff0000u); }
__device__ __forceinline__ float bf_round(float v) { return __bfloat162float(__float2bfloat16_rn(v)); }
__device__ __forceinline__ uint32_t pack_bf(float lo, float hi) { uint32_t r; asm("cvt.rn.bf16x2.f32 %0, %1, %2;" : "=r"(r) : "f"(hi), "f"(lo)); return r; }
__device__ __forceinline__ uint32_t pack_bf_relu(float lo, float hi) { uint32_t r; asm("cvt.rn.relu.bf16x2.f32 %0, %1, %2;" : "=r"(r) : "f"(hi), "f"(lo)); return r; }
__device__ __forceinline__ uint32_t bf_mul2(uint32_t a, uint32_t b) { uint32_t r; asm("mul.rn.bf16x2 %0, %1, %2;" : "=r"(r) : "r"(a), "r"(b)); return r; }
__device__ __forceinline__ uint32_t bf_add2(uint32_t a, uint32_t b) { uint32_t r; asm("add.rn.bf16x2 %0, %1, %2;" : "=r"(r) : "r"(a), "r"(b)); return r; }
__device__ __forceinline__ uint32_t ld_relaxed(const uint32_t* p) { uint32_t v; asm volatile("ld.relaxed.gpu.global.u32 %0, [%1];" : "=r"(v) : "l"(p) : "memory"); return v; }
__device__ __forceinline__ uint32_t ldg_u16(const void* p) { uint32_t v; asm volatile("ld.global.nc.u16 %0, [%1];" : "=r"(v) : "l"(p)); return v; }
__device__ __forceinline__ uint32_t ldg_nc(const void* p) { uint32_t v; asm volatile("ld.global.nc.u32 %0, [%1];" : "=r"(v) : "l"(p)); return v; }
__device__ __forceinline__ void st_relaxed(uint32_t* p, uint32_t v) { asm volatile("st.relaxed.gpu.global.u32 [%0], %1;" ::"l"(p), "r"(v) : "memory"); }
__device__ __forceinline__ uint32_t ld_acquire(const uint32_t* p) { uint32_t v; asm volatile("ld.acquire.gpu.global.u32 %0, [%1];" : "=r"(v) : "l"(p) : "memory"); return v; }
__device__ __forceinline__ void st_release(uint32_t* p, uint32_t v) {
  if (ABL & 16) asm volatile("st.relaxed.gpu.global.u32 [%0], %1;" ::"l"(p), "r"(v) : "memory");
  else asm volatile("st.release.gpu.global.u32 [%0], %1;" ::"l"(p), "r"(v) : "memory");
}
__device__ __forceinline__ uint2 ld_relaxed2(const uint2* p) { uint2 v; asm volatile("ld.relaxed.gpu.global.v2.u32 {%0,%1}, [%2];" : "=r"(v.x), "=r"(v.y) : "l"(p) : "memory"); return v; }
__device__ __forceinline__ void st_relaxed2(uint2* p, uint32_t a, uint32_t b) { asm volatile("st.relaxed.gpu.global.v2.u32 [%0], {%1,%2};" ::"l"(p), "r"(a), "r"(b) : "memory"); }
__device__ __forceinline__ uint4 ld_packet(const uint4* p) {
  uint4 v;
  asm volatile("{\n.reg .b128 t;\n.reg .b64 a, b;\nld.relaxed.gpu.global.b128 t, [%4];\nmov.b128 {a, b}, t;\nmov.b64 {%0, %1}, a;\nmov.b64 {%2, %3}, b;\n}"
               : "=r"(v.x), "=r"(v.y), "=r"(v.z), "=r"(v.w) : "l"(p) : "memory");
  return v;
}
__device__ __forceinline__ void st_packet(uint4* p, uint32_t x, uint32_t y, uint32_t z, uint32_t w) {
  asm volatile("{\n.reg .b128 t;\n.reg .b64 a, b;\nmov.b64 a, {%1, %2};\nmov.b64 b, {%3, %4};\nmov.b128 t, {a, b};\nst.relaxed.gpu.global.b128 [%0], t;\n}"
               ::"l"(p), "r"(x), "r"(y), "r"(z), "r"(w) : "memory");
}
__device__ __forceinline__ uint32_t tagw(float v, uint32_t tag) { return (__float_as_uint(v) & ~3u) | tag; }
struct cf { float r, i; };
__device__ __forceinline__ cf cmul(cf a, cf b) { return {a.r * b.r - a.i * b.i, a.r * b.i + a.i * b.r}; }
__device__ __forceinline__ cf csq(cf a) { return {a.r * a.r - a.i * a.i, 2.f * a.r * a.i}; }
__device__ __forceinline__ cf cfma(cf a, cf b, cf c) { return {fmaf(a.r, b.r, fmaf(-a.i, b.i, c.r)), fmaf(a.r, b.i, fmaf(a.i, b.r, c.i))}; }
__device__ __forceinline__ float silu_half(float h) { float t; asm("tanh.approx.f32 %0, %1;" : "=f"(t) : "f"(h)); return fmaf(h, t, h); }

template<int TA, int TB, uint32_t AHI, uint32_t BHI>
__device__ __forceinline__ void wgmma_n8(float (&d)[4], uint32_t alo, uint32_t blo, int scale_d) {
  asm volatile("{\n.reg .pred p;\n.reg .b64 da, db;\nsetp.ne.b32 p, %6, 0;\n"
    "mov.b64 da, {%4, %9};\nmov.b64 db, {%5, %10};\n"
    "wgmma.mma_async.sync.aligned.m64n8k16.f32.bf16.bf16 "
    "{%0, %1, %2, %3}, "
    "da, db, p, 1, 1, %7, %8;\n}\n"
    : "+f"(d[0]), "+f"(d[1]), "+f"(d[2]), "+f"(d[3])
    : "r"(alo), "r"(blo), "r"(scale_d), "n"(TA), "n"(TB), "n"(AHI), "n"(BHI));
}
template<int TA, int TB, uint32_t AHI, uint32_t BHI>
__device__ __forceinline__ void wgmma_n128(float (&d)[64], uint32_t alo, uint32_t blo, int scale_d) {
  asm volatile("{\n.reg .pred p;\n.reg .b64 da, db;\nsetp.ne.b32 p, %66, 0;\n"
    "mov.b64 da, {%64, %69};\nmov.b64 db, {%65, %70};\n"
    "wgmma.mma_async.sync.aligned.m64n128k16.f32.bf16.bf16 "
    "{%0, %1, %2, %3, %4, %5, %6, %7, %8, %9, %10, %11, %12, %13, %14, %15, %16, %17, %18, %19, "
    "%20, %21, %22, %23, %24, %25, %26, %27, %28, %29, %30, %31, %32, %33, %34, %35, %36, %37, %38, %39, "
    "%40, %41, %42, %43, %44, %45, %46, %47, %48, %49, %50, %51, %52, %53, %54, %55, %56, %57, %58, %59, "
    "%60, %61, %62, %63}, "
    "da, db, p, 1, 1, %67, %68;\n}\n"
    : "+f"(d[0]), "+f"(d[1]), "+f"(d[2]), "+f"(d[3]), "+f"(d[4]), "+f"(d[5]), "+f"(d[6]), "+f"(d[7]),
      "+f"(d[8]), "+f"(d[9]), "+f"(d[10]), "+f"(d[11]), "+f"(d[12]), "+f"(d[13]), "+f"(d[14]), "+f"(d[15]),
      "+f"(d[16]), "+f"(d[17]), "+f"(d[18]), "+f"(d[19]), "+f"(d[20]), "+f"(d[21]), "+f"(d[22]), "+f"(d[23]),
      "+f"(d[24]), "+f"(d[25]), "+f"(d[26]), "+f"(d[27]), "+f"(d[28]), "+f"(d[29]), "+f"(d[30]), "+f"(d[31]),
      "+f"(d[32]), "+f"(d[33]), "+f"(d[34]), "+f"(d[35]), "+f"(d[36]), "+f"(d[37]), "+f"(d[38]), "+f"(d[39]),
      "+f"(d[40]), "+f"(d[41]), "+f"(d[42]), "+f"(d[43]), "+f"(d[44]), "+f"(d[45]), "+f"(d[46]), "+f"(d[47]),
      "+f"(d[48]), "+f"(d[49]), "+f"(d[50]), "+f"(d[51]), "+f"(d[52]), "+f"(d[53]), "+f"(d[54]), "+f"(d[55]),
      "+f"(d[56]), "+f"(d[57]), "+f"(d[58]), "+f"(d[59]), "+f"(d[60]), "+f"(d[61]), "+f"(d[62]), "+f"(d[63])
    : "r"(alo), "r"(blo), "r"(scale_d), "n"(TA), "n"(TB), "n"(AHI), "n"(BHI));
}
template<int TA, int TB, uint32_t AHI, uint32_t BHI>
__device__ __forceinline__ void wgmma_n160(float (&d)[80], uint32_t alo, uint32_t blo, int scale_d) {
  asm volatile("{\n.reg .pred p;\n.reg .b64 da, db;\nsetp.ne.b32 p, %82, 0;\n"
    "mov.b64 da, {%80, %85};\nmov.b64 db, {%81, %86};\n"
    "wgmma.mma_async.sync.aligned.m64n160k16.f32.bf16.bf16 "
    "{%0, %1, %2, %3, %4, %5, %6, %7, %8, %9, %10, %11, %12, %13, %14, %15, %16, %17, %18, %19, "
    "%20, %21, %22, %23, %24, %25, %26, %27, %28, %29, %30, %31, %32, %33, %34, %35, %36, %37, %38, %39, "
    "%40, %41, %42, %43, %44, %45, %46, %47, %48, %49, %50, %51, %52, %53, %54, %55, %56, %57, %58, %59, "
    "%60, %61, %62, %63, %64, %65, %66, %67, %68, %69, %70, %71, %72, %73, %74, %75, %76, %77, %78, %79}, "
    "da, db, p, 1, 1, %83, %84;\n}\n"
    : "+f"(d[0]), "+f"(d[1]), "+f"(d[2]), "+f"(d[3]), "+f"(d[4]), "+f"(d[5]), "+f"(d[6]), "+f"(d[7]),
      "+f"(d[8]), "+f"(d[9]), "+f"(d[10]), "+f"(d[11]), "+f"(d[12]), "+f"(d[13]), "+f"(d[14]), "+f"(d[15]),
      "+f"(d[16]), "+f"(d[17]), "+f"(d[18]), "+f"(d[19]), "+f"(d[20]), "+f"(d[21]), "+f"(d[22]), "+f"(d[23]),
      "+f"(d[24]), "+f"(d[25]), "+f"(d[26]), "+f"(d[27]), "+f"(d[28]), "+f"(d[29]), "+f"(d[30]), "+f"(d[31]),
      "+f"(d[32]), "+f"(d[33]), "+f"(d[34]), "+f"(d[35]), "+f"(d[36]), "+f"(d[37]), "+f"(d[38]), "+f"(d[39]),
      "+f"(d[40]), "+f"(d[41]), "+f"(d[42]), "+f"(d[43]), "+f"(d[44]), "+f"(d[45]), "+f"(d[46]), "+f"(d[47]),
      "+f"(d[48]), "+f"(d[49]), "+f"(d[50]), "+f"(d[51]), "+f"(d[52]), "+f"(d[53]), "+f"(d[54]), "+f"(d[55]),
      "+f"(d[56]), "+f"(d[57]), "+f"(d[58]), "+f"(d[59]), "+f"(d[60]), "+f"(d[61]), "+f"(d[62]), "+f"(d[63]),
      "+f"(d[64]), "+f"(d[65]), "+f"(d[66]), "+f"(d[67]), "+f"(d[68]), "+f"(d[69]), "+f"(d[70]), "+f"(d[71]),
      "+f"(d[72]), "+f"(d[73]), "+f"(d[74]), "+f"(d[75]), "+f"(d[76]), "+f"(d[77]), "+f"(d[78]), "+f"(d[79])
    : "r"(alo), "r"(blo), "r"(scale_d), "n"(TA), "n"(TB), "n"(AHI), "n"(BHI));
}
template<int TA, int TB, uint32_t AHI, uint32_t BHI>
__device__ __forceinline__ void wgmma_n96(float (&d)[48], uint32_t alo, uint32_t blo, int scale_d) {
  asm volatile("{\n.reg .pred p;\n.reg .b64 da, db;\nsetp.ne.b32 p, %50, 0;\n"
    "mov.b64 da, {%48, %53};\nmov.b64 db, {%49, %54};\n"
    "wgmma.mma_async.sync.aligned.m64n96k16.f32.bf16.bf16 "
    "{%0, %1, %2, %3, %4, %5, %6, %7, %8, %9, %10, %11, %12, %13, %14, %15, %16, %17, %18, %19, "
    "%20, %21, %22, %23, %24, %25, %26, %27, %28, %29, %30, %31, %32, %33, %34, %35, %36, %37, %38, %39, "
    "%40, %41, %42, %43, %44, %45, %46, %47}, "
    "da, db, p, 1, 1, %51, %52;\n}\n"
    : "+f"(d[0]), "+f"(d[1]), "+f"(d[2]), "+f"(d[3]), "+f"(d[4]), "+f"(d[5]), "+f"(d[6]), "+f"(d[7]),
      "+f"(d[8]), "+f"(d[9]), "+f"(d[10]), "+f"(d[11]), "+f"(d[12]), "+f"(d[13]), "+f"(d[14]), "+f"(d[15]),
      "+f"(d[16]), "+f"(d[17]), "+f"(d[18]), "+f"(d[19]), "+f"(d[20]), "+f"(d[21]), "+f"(d[22]), "+f"(d[23]),
      "+f"(d[24]), "+f"(d[25]), "+f"(d[26]), "+f"(d[27]), "+f"(d[28]), "+f"(d[29]), "+f"(d[30]), "+f"(d[31]),
      "+f"(d[32]), "+f"(d[33]), "+f"(d[34]), "+f"(d[35]), "+f"(d[36]), "+f"(d[37]), "+f"(d[38]), "+f"(d[39]),
      "+f"(d[40]), "+f"(d[41]), "+f"(d[42]), "+f"(d[43]), "+f"(d[44]), "+f"(d[45]), "+f"(d[46]), "+f"(d[47])
    : "r"(alo), "r"(blo), "r"(scale_d), "n"(TA), "n"(TB), "n"(AHI), "n"(BHI));
}
template<int TA, int TB, uint32_t AHI, uint32_t BHI>
__device__ __forceinline__ void wgmma_n64(float (&d)[32], uint32_t alo, uint32_t blo, int scale_d) {
  asm volatile("{\n.reg .pred p;\n.reg .b64 da, db;\nsetp.ne.b32 p, %34, 0;\n"
    "mov.b64 da, {%32, %37};\nmov.b64 db, {%33, %38};\n"
    "wgmma.mma_async.sync.aligned.m64n64k16.f32.bf16.bf16 "
    "{%0, %1, %2, %3, %4, %5, %6, %7, %8, %9, %10, %11, %12, %13, %14, %15, %16, %17, %18, %19, "
    "%20, %21, %22, %23, %24, %25, %26, %27, %28, %29, %30, %31}, "
    "da, db, p, 1, 1, %35, %36;\n}\n"
    : "+f"(d[0]), "+f"(d[1]), "+f"(d[2]), "+f"(d[3]), "+f"(d[4]), "+f"(d[5]), "+f"(d[6]), "+f"(d[7]),
      "+f"(d[8]), "+f"(d[9]), "+f"(d[10]), "+f"(d[11]), "+f"(d[12]), "+f"(d[13]), "+f"(d[14]), "+f"(d[15]),
      "+f"(d[16]), "+f"(d[17]), "+f"(d[18]), "+f"(d[19]), "+f"(d[20]), "+f"(d[21]), "+f"(d[22]), "+f"(d[23]),
      "+f"(d[24]), "+f"(d[25]), "+f"(d[26]), "+f"(d[27]), "+f"(d[28]), "+f"(d[29]), "+f"(d[30]), "+f"(d[31])
    : "r"(alo), "r"(blo), "r"(scale_d), "n"(TA), "n"(TB), "n"(AHI), "n"(BHI));
}
template<uint32_t BHI>
__device__ __forceinline__ void wgmma_rs_n128(float (&d)[64], uint32_t a0, uint32_t a1, uint32_t blo) {
  asm volatile("{\n.reg .b64 db;\n.reg .b32 z;\nmov.b32 z, 0;\n"
    "mov.b64 db, {%66, %67};\n"
    "wgmma.mma_async.sync.aligned.m64n128k16.f32.bf16.bf16 "
    "{%0, %1, %2, %3, %4, %5, %6, %7, %8, %9, %10, %11, %12, %13, %14, %15, %16, %17, %18, %19, "
    "%20, %21, %22, %23, %24, %25, %26, %27, %28, %29, %30, %31, %32, %33, %34, %35, %36, %37, %38, %39, "
    "%40, %41, %42, %43, %44, %45, %46, %47, %48, %49, %50, %51, %52, %53, %54, %55, %56, %57, %58, %59, "
    "%60, %61, %62, %63}, "
    "{%64, %65, z, z}, db, 1, 1, 1, 0;\n}\n"
    : "+f"(d[0]), "+f"(d[1]), "+f"(d[2]), "+f"(d[3]), "+f"(d[4]), "+f"(d[5]), "+f"(d[6]), "+f"(d[7]),
      "+f"(d[8]), "+f"(d[9]), "+f"(d[10]), "+f"(d[11]), "+f"(d[12]), "+f"(d[13]), "+f"(d[14]), "+f"(d[15]),
      "+f"(d[16]), "+f"(d[17]), "+f"(d[18]), "+f"(d[19]), "+f"(d[20]), "+f"(d[21]), "+f"(d[22]), "+f"(d[23]),
      "+f"(d[24]), "+f"(d[25]), "+f"(d[26]), "+f"(d[27]), "+f"(d[28]), "+f"(d[29]), "+f"(d[30]), "+f"(d[31]),
      "+f"(d[32]), "+f"(d[33]), "+f"(d[34]), "+f"(d[35]), "+f"(d[36]), "+f"(d[37]), "+f"(d[38]), "+f"(d[39]),
      "+f"(d[40]), "+f"(d[41]), "+f"(d[42]), "+f"(d[43]), "+f"(d[44]), "+f"(d[45]), "+f"(d[46]), "+f"(d[47]),
      "+f"(d[48]), "+f"(d[49]), "+f"(d[50]), "+f"(d[51]), "+f"(d[52]), "+f"(d[53]), "+f"(d[54]), "+f"(d[55]),
      "+f"(d[56]), "+f"(d[57]), "+f"(d[58]), "+f"(d[59]), "+f"(d[60]), "+f"(d[61]), "+f"(d[62]), "+f"(d[63])
    : "r"(a0), "r"(a1), "r"(blo), "n"(BHI));
}
template<int TA, int TB, uint32_t AHI, uint32_t BHI, uint32_t A1, uint32_t B1, uint32_t B2>
__device__ __forceinline__ void kblock_n160(float (&d)[80], uint32_t alo, uint32_t blo, uint32_t nbar, uint32_t npar,
    uint32_t r1, uint32_t c1, uint32_t r2, uint32_t c2, uint32_t xbar) {
  asm volatile("{\n.reg .pred p, px, q;\n.reg .b64 da, db;\n.reg .b32 t, n;\n"
    "wgmma.fence.sync.aligned;\n"
    "add.u32 t, %80, 0*%93;\nmov.b64 da, {t, %91};\n"
    "add.u32 t, %81, 0*%94+0*%95;\nmov.b64 db, {t, %92};\n"
    "wgmma.mma_async.sync.aligned.m64n160k16.f32.bf16.bf16 "
    "{%0, %1, %2, %3, %4, %5, %6, %7, %8, %9, %10, %11, %12, %13, %14, %15, %16, %17, %18, %19, "
    "%20, %21, %22, %23, %24, %25, %26, %27, %28, %29, %30, %31, %32, %33, %34, %35, %36, %37, %38, %39, "
    "%40, %41, %42, %43, %44, %45, %46, %47, %48, %49, %50, %51, %52, %53, %54, %55, %56, %57, %58, %59, "
    "%60, %61, %62, %63, %64, %65, %66, %67, %68, %69, %70, %71, %72, %73, %74, %75, %76, %77, %78, %79}, "
    "da, db, 1, 1, 1, %89, %90;\n"
    "mbarrier.try_wait.parity.shared::cta.b64 p, [%82], %83;\n"
    "add.u32 t, %80, 1*%93;\nmov.b64 da, {t, %91};\n"
    "add.u32 t, %81, 1*%94+0*%95;\nmov.b64 db, {t, %92};\n"
    "wgmma.mma_async.sync.aligned.m64n160k16.f32.bf16.bf16 "
    "{%0, %1, %2, %3, %4, %5, %6, %7, %8, %9, %10, %11, %12, %13, %14, %15, %16, %17, %18, %19, "
    "%20, %21, %22, %23, %24, %25, %26, %27, %28, %29, %30, %31, %32, %33, %34, %35, %36, %37, %38, %39, "
    "%40, %41, %42, %43, %44, %45, %46, %47, %48, %49, %50, %51, %52, %53, %54, %55, %56, %57, %58, %59, "
    "%60, %61, %62, %63, %64, %65, %66, %67, %68, %69, %70, %71, %72, %73, %74, %75, %76, %77, %78, %79}, "
    "da, db, 1, 1, 1, %89, %90;\n"
    "add.u32 t, %80, 2*%93;\nmov.b64 da, {t, %91};\n"
    "add.u32 t, %81, 0*%94+1*%95;\nmov.b64 db, {t, %92};\n"
    "wgmma.mma_async.sync.aligned.m64n160k16.f32.bf16.bf16 "
    "{%0, %1, %2, %3, %4, %5, %6, %7, %8, %9, %10, %11, %12, %13, %14, %15, %16, %17, %18, %19, "
    "%20, %21, %22, %23, %24, %25, %26, %27, %28, %29, %30, %31, %32, %33, %34, %35, %36, %37, %38, %39, "
    "%40, %41, %42, %43, %44, %45, %46, %47, %48, %49, %50, %51, %52, %53, %54, %55, %56, %57, %58, %59, "
    "%60, %61, %62, %63, %64, %65, %66, %67, %68, %69, %70, %71, %72, %73, %74, %75, %76, %77, %78, %79}, "
    "da, db, 1, 1, 1, %89, %90;\n"
    "add.u32 t, %80, 3*%93;\nmov.b64 da, {t, %91};\n"
    "add.u32 t, %81, 1*%94+1*%95;\nmov.b64 db, {t, %92};\n"
    "wgmma.mma_async.sync.aligned.m64n160k16.f32.bf16.bf16 "
    "{%0, %1, %2, %3, %4, %5, %6, %7, %8, %9, %10, %11, %12, %13, %14, %15, %16, %17, %18, %19, "
    "%20, %21, %22, %23, %24, %25, %26, %27, %28, %29, %30, %31, %32, %33, %34, %35, %36, %37, %38, %39, "
    "%40, %41, %42, %43, %44, %45, %46, %47, %48, %49, %50, %51, %52, %53, %54, %55, %56, %57, %58, %59, "
    "%60, %61, %62, %63, %64, %65, %66, %67, %68, %69, %70, %71, %72, %73, %74, %75, %76, %77, %78, %79}, "
    "da, db, 1, 1, 1, %89, %90;\n"
    "wgmma.commit_group.sync.aligned;\nwgmma.wait_group.sync.aligned 1;\n"
    "setp.ne.u32 q, %85, 0;\n@q mbarrier.arrive.shared::cluster.b64 _, [%84];\n"
    "@p bra LDA;\nmov.u32 n, 0;\nLWA:\nmbarrier.try_wait.parity.shared::cta.b64 p, [%82], %83;\n@p bra LDA;\n"
    "add.u32 n, n, 1;\nsetp.lt.u32 p, n, 0x4000;\n@p bra LWA;\nLDA:\n"
    "}"
    : "+f"(d[0]), "+f"(d[1]), "+f"(d[2]), "+f"(d[3]), "+f"(d[4]), "+f"(d[5]), "+f"(d[6]), "+f"(d[7]),
      "+f"(d[8]), "+f"(d[9]), "+f"(d[10]), "+f"(d[11]), "+f"(d[12]), "+f"(d[13]), "+f"(d[14]), "+f"(d[15]),
      "+f"(d[16]), "+f"(d[17]), "+f"(d[18]), "+f"(d[19]), "+f"(d[20]), "+f"(d[21]), "+f"(d[22]), "+f"(d[23]),
      "+f"(d[24]), "+f"(d[25]), "+f"(d[26]), "+f"(d[27]), "+f"(d[28]), "+f"(d[29]), "+f"(d[30]), "+f"(d[31]),
      "+f"(d[32]), "+f"(d[33]), "+f"(d[34]), "+f"(d[35]), "+f"(d[36]), "+f"(d[37]), "+f"(d[38]), "+f"(d[39]),
      "+f"(d[40]), "+f"(d[41]), "+f"(d[42]), "+f"(d[43]), "+f"(d[44]), "+f"(d[45]), "+f"(d[46]), "+f"(d[47]),
      "+f"(d[48]), "+f"(d[49]), "+f"(d[50]), "+f"(d[51]), "+f"(d[52]), "+f"(d[53]), "+f"(d[54]), "+f"(d[55]),
      "+f"(d[56]), "+f"(d[57]), "+f"(d[58]), "+f"(d[59]), "+f"(d[60]), "+f"(d[61]), "+f"(d[62]), "+f"(d[63]),
      "+f"(d[64]), "+f"(d[65]), "+f"(d[66]), "+f"(d[67]), "+f"(d[68]), "+f"(d[69]), "+f"(d[70]), "+f"(d[71]),
      "+f"(d[72]), "+f"(d[73]), "+f"(d[74]), "+f"(d[75]), "+f"(d[76]), "+f"(d[77]), "+f"(d[78]), "+f"(d[79])
    : "r"(alo), "r"(blo), "r"(nbar), "r"(npar), "r"(r1), "r"(c1), "r"(r2), "r"(c2), "r"(xbar),
      "n"(TA), "n"(TB), "n"(AHI), "n"(BHI), "n"(A1), "n"(B1), "n"(B2) : "memory");
}
template<int TA, uint32_t AHI, uint32_t BHI, uint32_t A1, uint32_t AH>
__device__ __forceinline__ void stage_plain(float (&d)[64], uint32_t alo, uint32_t blo, uint32_t nbar, uint32_t npar,
    uint32_t r1, uint32_t c1, uint32_t r2, uint32_t c2, uint32_t xb0, uint32_t xb1) {
  asm volatile("{\n.reg .pred p, px, q;\n.reg .b64 da, db;\n.reg .b32 t, n;\n"
    "wgmma.wait_group.sync.aligned 1;\n"
    "wgmma.fence.sync.aligned;\n"
    "add.u32 t, %64, 0*%77+0*%78;\nmov.b64 da, {t, %75};\n"
    "add.u32 t, %65, 0;\nmov.b64 db, {t, %76};\n"
    "wgmma.mma_async.sync.aligned.m64n128k16.f32.bf16.bf16 "
    "{%0, %1, %2, %3, %4, %5, %6, %7, %8, %9, %10, %11, %12, %13, %14, %15, %16, %17, %18, %19, "
    "%20, %21, %22, %23, %24, %25, %26, %27, %28, %29, %30, %31, %32, %33, %34, %35, %36, %37, %38, %39, "
    "%40, %41, %42, %43, %44, %45, %46, %47, %48, %49, %50, %51, %52, %53, %54, %55, %56, %57, %58, %59, "
    "%60, %61, %62, %63}, "
    "da, db, 1, 1, 1, %74, 0;\n"
    "add.u32 t, %64, 1*%77+0*%78;\nmov.b64 da, {t, %75};\n"
    "add.u32 t, %65, 2;\nmov.b64 db, {t, %76};\n"
    "wgmma.mma_async.sync.aligned.m64n128k16.f32.bf16.bf16 "
    "{%0, %1, %2, %3, %4, %5, %6, %7, %8, %9, %10, %11, %12, %13, %14, %15, %16, %17, %18, %19, "
    "%20, %21, %22, %23, %24, %25, %26, %27, %28, %29, %30, %31, %32, %33, %34, %35, %36, %37, %38, %39, "
    "%40, %41, %42, %43, %44, %45, %46, %47, %48, %49, %50, %51, %52, %53, %54, %55, %56, %57, %58, %59, "
    "%60, %61, %62, %63}, "
    "da, db, 1, 1, 1, %74, 0;\n"
    "add.u32 t, %64, 2*%77+0*%78;\nmov.b64 da, {t, %75};\n"
    "add.u32 t, %65, 4;\nmov.b64 db, {t, %76};\n"
    "wgmma.mma_async.sync.aligned.m64n128k16.f32.bf16.bf16 "
    "{%0, %1, %2, %3, %4, %5, %6, %7, %8, %9, %10, %11, %12, %13, %14, %15, %16, %17, %18, %19, "
    "%20, %21, %22, %23, %24, %25, %26, %27, %28, %29, %30, %31, %32, %33, %34, %35, %36, %37, %38, %39, "
    "%40, %41, %42, %43, %44, %45, %46, %47, %48, %49, %50, %51, %52, %53, %54, %55, %56, %57, %58, %59, "
    "%60, %61, %62, %63}, "
    "da, db, 1, 1, 1, %74, 0;\n"
    "add.u32 t, %64, 3*%77+0*%78;\nmov.b64 da, {t, %75};\n"
    "add.u32 t, %65, 6;\nmov.b64 db, {t, %76};\n"
    "wgmma.mma_async.sync.aligned.m64n128k16.f32.bf16.bf16 "
    "{%0, %1, %2, %3, %4, %5, %6, %7, %8, %9, %10, %11, %12, %13, %14, %15, %16, %17, %18, %19, "
    "%20, %21, %22, %23, %24, %25, %26, %27, %28, %29, %30, %31, %32, %33, %34, %35, %36, %37, %38, %39, "
    "%40, %41, %42, %43, %44, %45, %46, %47, %48, %49, %50, %51, %52, %53, %54, %55, %56, %57, %58, %59, "
    "%60, %61, %62, %63}, "
    "da, db, 1, 1, 1, %74, 0;\n"
    "wgmma.commit_group.sync.aligned;\n"
    "wgmma.wait_group.sync.aligned 1;\n"
    "setp.ne.u32 q, %69, 0;\n@q mbarrier.arrive.shared::cluster.b64 _, [%68];\n"
    "wgmma.fence.sync.aligned;\n"
    "add.u32 t, %64, 0*%77+1*%78;\nmov.b64 da, {t, %75};\n"
    "add.u32 t, %65, 1024;\nmov.b64 db, {t, %76};\n"
    "wgmma.mma_async.sync.aligned.m64n128k16.f32.bf16.bf16 "
    "{%0, %1, %2, %3, %4, %5, %6, %7, %8, %9, %10, %11, %12, %13, %14, %15, %16, %17, %18, %19, "
    "%20, %21, %22, %23, %24, %25, %26, %27, %28, %29, %30, %31, %32, %33, %34, %35, %36, %37, %38, %39, "
    "%40, %41, %42, %43, %44, %45, %46, %47, %48, %49, %50, %51, %52, %53, %54, %55, %56, %57, %58, %59, "
    "%60, %61, %62, %63}, "
    "da, db, 1, 1, 1, %74, 0;\n"
    "mbarrier.try_wait.parity.shared::cta.b64 p, [%66], %67;\n"
    "add.u32 t, %64, 1*%77+1*%78;\nmov.b64 da, {t, %75};\n"
    "add.u32 t, %65, 1026;\nmov.b64 db, {t, %76};\n"
    "wgmma.mma_async.sync.aligned.m64n128k16.f32.bf16.bf16 "
    "{%0, %1, %2, %3, %4, %5, %6, %7, %8, %9, %10, %11, %12, %13, %14, %15, %16, %17, %18, %19, "
    "%20, %21, %22, %23, %24, %25, %26, %27, %28, %29, %30, %31, %32, %33, %34, %35, %36, %37, %38, %39, "
    "%40, %41, %42, %43, %44, %45, %46, %47, %48, %49, %50, %51, %52, %53, %54, %55, %56, %57, %58, %59, "
    "%60, %61, %62, %63}, "
    "da, db, 1, 1, 1, %74, 0;\n"
    "add.u32 t, %64, 2*%77+1*%78;\nmov.b64 da, {t, %75};\n"
    "add.u32 t, %65, 1028;\nmov.b64 db, {t, %76};\n"
    "wgmma.mma_async.sync.aligned.m64n128k16.f32.bf16.bf16 "
    "{%0, %1, %2, %3, %4, %5, %6, %7, %8, %9, %10, %11, %12, %13, %14, %15, %16, %17, %18, %19, "
    "%20, %21, %22, %23, %24, %25, %26, %27, %28, %29, %30, %31, %32, %33, %34, %35, %36, %37, %38, %39, "
    "%40, %41, %42, %43, %44, %45, %46, %47, %48, %49, %50, %51, %52, %53, %54, %55, %56, %57, %58, %59, "
    "%60, %61, %62, %63}, "
    "da, db, 1, 1, 1, %74, 0;\n"
    "add.u32 t, %64, 3*%77+1*%78;\nmov.b64 da, {t, %75};\n"
    "add.u32 t, %65, 1030;\nmov.b64 db, {t, %76};\n"
    "wgmma.mma_async.sync.aligned.m64n128k16.f32.bf16.bf16 "
    "{%0, %1, %2, %3, %4, %5, %6, %7, %8, %9, %10, %11, %12, %13, %14, %15, %16, %17, %18, %19, "
    "%20, %21, %22, %23, %24, %25, %26, %27, %28, %29, %30, %31, %32, %33, %34, %35, %36, %37, %38, %39, "
    "%40, %41, %42, %43, %44, %45, %46, %47, %48, %49, %50, %51, %52, %53, %54, %55, %56, %57, %58, %59, "
    "%60, %61, %62, %63}, "
    "da, db, 1, 1, 1, %74, 0;\n"
    "wgmma.commit_group.sync.aligned;\n"
    "@p bra LDA;\nmov.u32 n, 0;\nLWA:\nmbarrier.try_wait.parity.shared::cta.b64 p, [%66], %67;\n@p bra LDA;\n"
    "add.u32 n, n, 1;\nsetp.lt.u32 p, n, 0x4000;\n@p bra LWA;\nLDA:\n"
    "}"
    : "+f"(d[0]), "+f"(d[1]), "+f"(d[2]), "+f"(d[3]), "+f"(d[4]), "+f"(d[5]), "+f"(d[6]), "+f"(d[7]),
      "+f"(d[8]), "+f"(d[9]), "+f"(d[10]), "+f"(d[11]), "+f"(d[12]), "+f"(d[13]), "+f"(d[14]), "+f"(d[15]),
      "+f"(d[16]), "+f"(d[17]), "+f"(d[18]), "+f"(d[19]), "+f"(d[20]), "+f"(d[21]), "+f"(d[22]), "+f"(d[23]),
      "+f"(d[24]), "+f"(d[25]), "+f"(d[26]), "+f"(d[27]), "+f"(d[28]), "+f"(d[29]), "+f"(d[30]), "+f"(d[31]),
      "+f"(d[32]), "+f"(d[33]), "+f"(d[34]), "+f"(d[35]), "+f"(d[36]), "+f"(d[37]), "+f"(d[38]), "+f"(d[39]),
      "+f"(d[40]), "+f"(d[41]), "+f"(d[42]), "+f"(d[43]), "+f"(d[44]), "+f"(d[45]), "+f"(d[46]), "+f"(d[47]),
      "+f"(d[48]), "+f"(d[49]), "+f"(d[50]), "+f"(d[51]), "+f"(d[52]), "+f"(d[53]), "+f"(d[54]), "+f"(d[55]),
      "+f"(d[56]), "+f"(d[57]), "+f"(d[58]), "+f"(d[59]), "+f"(d[60]), "+f"(d[61]), "+f"(d[62]), "+f"(d[63])
    : "r"(alo), "r"(blo), "r"(nbar), "r"(npar), "r"(r1), "r"(c1), "r"(r2), "r"(c2), "r"(xb0), "r"(xb1),
      "n"(TA), "n"(AHI), "n"(BHI), "n"(A1), "n"(AH) : "memory");
}
template<int TA, uint32_t AHI, uint32_t BHI, uint32_t A1, uint32_t AH>
__device__ __forceinline__ void stage_first(float (&d)[64], uint32_t alo, uint32_t blo, uint32_t nbar, uint32_t npar,
    uint32_t r1, uint32_t c1, uint32_t r2, uint32_t c2, uint32_t xb0, uint32_t xb1) {
  asm volatile("{\n.reg .pred p, px, q;\n.reg .b64 da, db;\n.reg .b32 t, n;\n"
    "wgmma.wait_group.sync.aligned 1;\n"
    "wgmma.fence.sync.aligned;\n"
    "add.u32 t, %64, 0*%77+0*%78;\nmov.b64 da, {t, %75};\n"
    "add.u32 t, %65, 0;\nmov.b64 db, {t, %76};\n"
    "wgmma.mma_async.sync.aligned.m64n128k16.f32.bf16.bf16 "
    "{%0, %1, %2, %3, %4, %5, %6, %7, %8, %9, %10, %11, %12, %13, %14, %15, %16, %17, %18, %19, "
    "%20, %21, %22, %23, %24, %25, %26, %27, %28, %29, %30, %31, %32, %33, %34, %35, %36, %37, %38, %39, "
    "%40, %41, %42, %43, %44, %45, %46, %47, %48, %49, %50, %51, %52, %53, %54, %55, %56, %57, %58, %59, "
    "%60, %61, %62, %63}, "
    "da, db, 1, 1, 1, %74, 0;\n"
    "mbarrier.try_wait.parity.shared::cta.b64 px, [%72], 0;\n"
    "add.u32 t, %64, 1*%77+0*%78;\nmov.b64 da, {t, %75};\n"
    "add.u32 t, %65, 2;\nmov.b64 db, {t, %76};\n"
    "wgmma.mma_async.sync.aligned.m64n128k16.f32.bf16.bf16 "
    "{%0, %1, %2, %3, %4, %5, %6, %7, %8, %9, %10, %11, %12, %13, %14, %15, %16, %17, %18, %19, "
    "%20, %21, %22, %23, %24, %25, %26, %27, %28, %29, %30, %31, %32, %33, %34, %35, %36, %37, %38, %39, "
    "%40, %41, %42, %43, %44, %45, %46, %47, %48, %49, %50, %51, %52, %53, %54, %55, %56, %57, %58, %59, "
    "%60, %61, %62, %63}, "
    "da, db, 1, 1, 1, %74, 0;\n"
    "add.u32 t, %64, 2*%77+0*%78;\nmov.b64 da, {t, %75};\n"
    "add.u32 t, %65, 4;\nmov.b64 db, {t, %76};\n"
    "wgmma.mma_async.sync.aligned.m64n128k16.f32.bf16.bf16 "
    "{%0, %1, %2, %3, %4, %5, %6, %7, %8, %9, %10, %11, %12, %13, %14, %15, %16, %17, %18, %19, "
    "%20, %21, %22, %23, %24, %25, %26, %27, %28, %29, %30, %31, %32, %33, %34, %35, %36, %37, %38, %39, "
    "%40, %41, %42, %43, %44, %45, %46, %47, %48, %49, %50, %51, %52, %53, %54, %55, %56, %57, %58, %59, "
    "%60, %61, %62, %63}, "
    "da, db, 1, 1, 1, %74, 0;\n"
    "add.u32 t, %64, 3*%77+0*%78;\nmov.b64 da, {t, %75};\n"
    "add.u32 t, %65, 6;\nmov.b64 db, {t, %76};\n"
    "wgmma.mma_async.sync.aligned.m64n128k16.f32.bf16.bf16 "
    "{%0, %1, %2, %3, %4, %5, %6, %7, %8, %9, %10, %11, %12, %13, %14, %15, %16, %17, %18, %19, "
    "%20, %21, %22, %23, %24, %25, %26, %27, %28, %29, %30, %31, %32, %33, %34, %35, %36, %37, %38, %39, "
    "%40, %41, %42, %43, %44, %45, %46, %47, %48, %49, %50, %51, %52, %53, %54, %55, %56, %57, %58, %59, "
    "%60, %61, %62, %63}, "
    "da, db, 1, 1, 1, %74, 0;\n"
    "wgmma.commit_group.sync.aligned;\n"
    "@px bra LDX0;\nmov.u32 n, 0;\nLWX0:\nmbarrier.try_wait.parity.shared::cta.b64 px, [%72], 0;\n@px bra LDX0;\n"
    "add.u32 n, n, 1;\nsetp.lt.u32 px, n, 0x4000;\n@px bra LWX0;\nLDX0:\n"
    "wgmma.wait_group.sync.aligned 1;\n"
    "setp.ne.u32 q, %69, 0;\n@q mbarrier.arrive.shared::cluster.b64 _, [%68];\n"
    "wgmma.fence.sync.aligned;\n"
    "add.u32 t, %64, 0*%77+1*%78;\nmov.b64 da, {t, %75};\n"
    "add.u32 t, %65, 1024;\nmov.b64 db, {t, %76};\n"
    "wgmma.mma_async.sync.aligned.m64n128k16.f32.bf16.bf16 "
    "{%0, %1, %2, %3, %4, %5, %6, %7, %8, %9, %10, %11, %12, %13, %14, %15, %16, %17, %18, %19, "
    "%20, %21, %22, %23, %24, %25, %26, %27, %28, %29, %30, %31, %32, %33, %34, %35, %36, %37, %38, %39, "
    "%40, %41, %42, %43, %44, %45, %46, %47, %48, %49, %50, %51, %52, %53, %54, %55, %56, %57, %58, %59, "
    "%60, %61, %62, %63}, "
    "da, db, 1, 1, 1, %74, 0;\n"
    "mbarrier.try_wait.parity.shared::cta.b64 p, [%66], %67;\n"
    "mbarrier.try_wait.parity.shared::cta.b64 px, [%73], 0;\n"
    "add.u32 t, %64, 1*%77+1*%78;\nmov.b64 da, {t, %75};\n"
    "add.u32 t, %65, 1026;\nmov.b64 db, {t, %76};\n"
    "wgmma.mma_async.sync.aligned.m64n128k16.f32.bf16.bf16 "
    "{%0, %1, %2, %3, %4, %5, %6, %7, %8, %9, %10, %11, %12, %13, %14, %15, %16, %17, %18, %19, "
    "%20, %21, %22, %23, %24, %25, %26, %27, %28, %29, %30, %31, %32, %33, %34, %35, %36, %37, %38, %39, "
    "%40, %41, %42, %43, %44, %45, %46, %47, %48, %49, %50, %51, %52, %53, %54, %55, %56, %57, %58, %59, "
    "%60, %61, %62, %63}, "
    "da, db, 1, 1, 1, %74, 0;\n"
    "add.u32 t, %64, 2*%77+1*%78;\nmov.b64 da, {t, %75};\n"
    "add.u32 t, %65, 1028;\nmov.b64 db, {t, %76};\n"
    "wgmma.mma_async.sync.aligned.m64n128k16.f32.bf16.bf16 "
    "{%0, %1, %2, %3, %4, %5, %6, %7, %8, %9, %10, %11, %12, %13, %14, %15, %16, %17, %18, %19, "
    "%20, %21, %22, %23, %24, %25, %26, %27, %28, %29, %30, %31, %32, %33, %34, %35, %36, %37, %38, %39, "
    "%40, %41, %42, %43, %44, %45, %46, %47, %48, %49, %50, %51, %52, %53, %54, %55, %56, %57, %58, %59, "
    "%60, %61, %62, %63}, "
    "da, db, 1, 1, 1, %74, 0;\n"
    "add.u32 t, %64, 3*%77+1*%78;\nmov.b64 da, {t, %75};\n"
    "add.u32 t, %65, 1030;\nmov.b64 db, {t, %76};\n"
    "wgmma.mma_async.sync.aligned.m64n128k16.f32.bf16.bf16 "
    "{%0, %1, %2, %3, %4, %5, %6, %7, %8, %9, %10, %11, %12, %13, %14, %15, %16, %17, %18, %19, "
    "%20, %21, %22, %23, %24, %25, %26, %27, %28, %29, %30, %31, %32, %33, %34, %35, %36, %37, %38, %39, "
    "%40, %41, %42, %43, %44, %45, %46, %47, %48, %49, %50, %51, %52, %53, %54, %55, %56, %57, %58, %59, "
    "%60, %61, %62, %63}, "
    "da, db, 1, 1, 1, %74, 0;\n"
    "wgmma.commit_group.sync.aligned;\n"
    "@p bra LDA;\nmov.u32 n, 0;\nLWA:\nmbarrier.try_wait.parity.shared::cta.b64 p, [%66], %67;\n@p bra LDA;\n"
    "add.u32 n, n, 1;\nsetp.lt.u32 p, n, 0x4000;\n@p bra LWA;\nLDA:\n"
    "@px bra LDX1;\nmov.u32 n, 0;\nLWX1:\nmbarrier.try_wait.parity.shared::cta.b64 px, [%73], 0;\n@px bra LDX1;\n"
    "add.u32 n, n, 1;\nsetp.lt.u32 px, n, 0x4000;\n@px bra LWX1;\nLDX1:\n"
    "}"
    : "+f"(d[0]), "+f"(d[1]), "+f"(d[2]), "+f"(d[3]), "+f"(d[4]), "+f"(d[5]), "+f"(d[6]), "+f"(d[7]),
      "+f"(d[8]), "+f"(d[9]), "+f"(d[10]), "+f"(d[11]), "+f"(d[12]), "+f"(d[13]), "+f"(d[14]), "+f"(d[15]),
      "+f"(d[16]), "+f"(d[17]), "+f"(d[18]), "+f"(d[19]), "+f"(d[20]), "+f"(d[21]), "+f"(d[22]), "+f"(d[23]),
      "+f"(d[24]), "+f"(d[25]), "+f"(d[26]), "+f"(d[27]), "+f"(d[28]), "+f"(d[29]), "+f"(d[30]), "+f"(d[31]),
      "+f"(d[32]), "+f"(d[33]), "+f"(d[34]), "+f"(d[35]), "+f"(d[36]), "+f"(d[37]), "+f"(d[38]), "+f"(d[39]),
      "+f"(d[40]), "+f"(d[41]), "+f"(d[42]), "+f"(d[43]), "+f"(d[44]), "+f"(d[45]), "+f"(d[46]), "+f"(d[47]),
      "+f"(d[48]), "+f"(d[49]), "+f"(d[50]), "+f"(d[51]), "+f"(d[52]), "+f"(d[53]), "+f"(d[54]), "+f"(d[55]),
      "+f"(d[56]), "+f"(d[57]), "+f"(d[58]), "+f"(d[59]), "+f"(d[60]), "+f"(d[61]), "+f"(d[62]), "+f"(d[63])
    : "r"(alo), "r"(blo), "r"(nbar), "r"(npar), "r"(r1), "r"(c1), "r"(r2), "r"(c2), "r"(xb0), "r"(xb1),
      "n"(TA), "n"(AHI), "n"(BHI), "n"(A1), "n"(AH) : "memory");
}
template<int TA, uint32_t AHI, uint32_t BHI, uint32_t A1, uint32_t AH>
__device__ __forceinline__ void stage_xfree(float (&d)[64], uint32_t alo, uint32_t blo, uint32_t nbar, uint32_t npar,
    uint32_t r1, uint32_t c1, uint32_t r2, uint32_t c2, uint32_t xb0, uint32_t xb1) {
  asm volatile("{\n.reg .pred p, px, q;\n.reg .b64 da, db;\n.reg .b32 t, n;\n"
    "wgmma.wait_group.sync.aligned 1;\n"
    "wgmma.fence.sync.aligned;\n"
    "add.u32 t, %64, 0*%77+0*%78;\nmov.b64 da, {t, %75};\n"
    "add.u32 t, %65, 0;\nmov.b64 db, {t, %76};\n"
    "wgmma.mma_async.sync.aligned.m64n128k16.f32.bf16.bf16 "
    "{%0, %1, %2, %3, %4, %5, %6, %7, %8, %9, %10, %11, %12, %13, %14, %15, %16, %17, %18, %19, "
    "%20, %21, %22, %23, %24, %25, %26, %27, %28, %29, %30, %31, %32, %33, %34, %35, %36, %37, %38, %39, "
    "%40, %41, %42, %43, %44, %45, %46, %47, %48, %49, %50, %51, %52, %53, %54, %55, %56, %57, %58, %59, "
    "%60, %61, %62, %63}, "
    "da, db, 1, 1, 1, %74, 0;\n"
    "add.u32 t, %64, 1*%77+0*%78;\nmov.b64 da, {t, %75};\n"
    "add.u32 t, %65, 2;\nmov.b64 db, {t, %76};\n"
    "wgmma.mma_async.sync.aligned.m64n128k16.f32.bf16.bf16 "
    "{%0, %1, %2, %3, %4, %5, %6, %7, %8, %9, %10, %11, %12, %13, %14, %15, %16, %17, %18, %19, "
    "%20, %21, %22, %23, %24, %25, %26, %27, %28, %29, %30, %31, %32, %33, %34, %35, %36, %37, %38, %39, "
    "%40, %41, %42, %43, %44, %45, %46, %47, %48, %49, %50, %51, %52, %53, %54, %55, %56, %57, %58, %59, "
    "%60, %61, %62, %63}, "
    "da, db, 1, 1, 1, %74, 0;\n"
    "add.u32 t, %64, 2*%77+0*%78;\nmov.b64 da, {t, %75};\n"
    "add.u32 t, %65, 4;\nmov.b64 db, {t, %76};\n"
    "wgmma.mma_async.sync.aligned.m64n128k16.f32.bf16.bf16 "
    "{%0, %1, %2, %3, %4, %5, %6, %7, %8, %9, %10, %11, %12, %13, %14, %15, %16, %17, %18, %19, "
    "%20, %21, %22, %23, %24, %25, %26, %27, %28, %29, %30, %31, %32, %33, %34, %35, %36, %37, %38, %39, "
    "%40, %41, %42, %43, %44, %45, %46, %47, %48, %49, %50, %51, %52, %53, %54, %55, %56, %57, %58, %59, "
    "%60, %61, %62, %63}, "
    "da, db, 1, 1, 1, %74, 0;\n"
    "add.u32 t, %64, 3*%77+0*%78;\nmov.b64 da, {t, %75};\n"
    "add.u32 t, %65, 6;\nmov.b64 db, {t, %76};\n"
    "wgmma.mma_async.sync.aligned.m64n128k16.f32.bf16.bf16 "
    "{%0, %1, %2, %3, %4, %5, %6, %7, %8, %9, %10, %11, %12, %13, %14, %15, %16, %17, %18, %19, "
    "%20, %21, %22, %23, %24, %25, %26, %27, %28, %29, %30, %31, %32, %33, %34, %35, %36, %37, %38, %39, "
    "%40, %41, %42, %43, %44, %45, %46, %47, %48, %49, %50, %51, %52, %53, %54, %55, %56, %57, %58, %59, "
    "%60, %61, %62, %63}, "
    "da, db, 1, 1, 1, %74, 0;\n"
    "wgmma.commit_group.sync.aligned;\n"
    "setp.ne.u32 q, %71, 0;\n@q mbarrier.arrive.shared::cluster.b64 _, [%70];\n"
    "wgmma.wait_group.sync.aligned 1;\n"
    "setp.ne.u32 q, %69, 0;\n@q mbarrier.arrive.shared::cluster.b64 _, [%68];\n"
    "wgmma.fence.sync.aligned;\n"
    "add.u32 t, %64, 0*%77+1*%78;\nmov.b64 da, {t, %75};\n"
    "add.u32 t, %65, 1024;\nmov.b64 db, {t, %76};\n"
    "wgmma.mma_async.sync.aligned.m64n128k16.f32.bf16.bf16 "
    "{%0, %1, %2, %3, %4, %5, %6, %7, %8, %9, %10, %11, %12, %13, %14, %15, %16, %17, %18, %19, "
    "%20, %21, %22, %23, %24, %25, %26, %27, %28, %29, %30, %31, %32, %33, %34, %35, %36, %37, %38, %39, "
    "%40, %41, %42, %43, %44, %45, %46, %47, %48, %49, %50, %51, %52, %53, %54, %55, %56, %57, %58, %59, "
    "%60, %61, %62, %63}, "
    "da, db, 1, 1, 1, %74, 0;\n"
    "mbarrier.try_wait.parity.shared::cta.b64 p, [%66], %67;\n"
    "add.u32 t, %64, 1*%77+1*%78;\nmov.b64 da, {t, %75};\n"
    "add.u32 t, %65, 1026;\nmov.b64 db, {t, %76};\n"
    "wgmma.mma_async.sync.aligned.m64n128k16.f32.bf16.bf16 "
    "{%0, %1, %2, %3, %4, %5, %6, %7, %8, %9, %10, %11, %12, %13, %14, %15, %16, %17, %18, %19, "
    "%20, %21, %22, %23, %24, %25, %26, %27, %28, %29, %30, %31, %32, %33, %34, %35, %36, %37, %38, %39, "
    "%40, %41, %42, %43, %44, %45, %46, %47, %48, %49, %50, %51, %52, %53, %54, %55, %56, %57, %58, %59, "
    "%60, %61, %62, %63}, "
    "da, db, 1, 1, 1, %74, 0;\n"
    "add.u32 t, %64, 2*%77+1*%78;\nmov.b64 da, {t, %75};\n"
    "add.u32 t, %65, 1028;\nmov.b64 db, {t, %76};\n"
    "wgmma.mma_async.sync.aligned.m64n128k16.f32.bf16.bf16 "
    "{%0, %1, %2, %3, %4, %5, %6, %7, %8, %9, %10, %11, %12, %13, %14, %15, %16, %17, %18, %19, "
    "%20, %21, %22, %23, %24, %25, %26, %27, %28, %29, %30, %31, %32, %33, %34, %35, %36, %37, %38, %39, "
    "%40, %41, %42, %43, %44, %45, %46, %47, %48, %49, %50, %51, %52, %53, %54, %55, %56, %57, %58, %59, "
    "%60, %61, %62, %63}, "
    "da, db, 1, 1, 1, %74, 0;\n"
    "add.u32 t, %64, 3*%77+1*%78;\nmov.b64 da, {t, %75};\n"
    "add.u32 t, %65, 1030;\nmov.b64 db, {t, %76};\n"
    "wgmma.mma_async.sync.aligned.m64n128k16.f32.bf16.bf16 "
    "{%0, %1, %2, %3, %4, %5, %6, %7, %8, %9, %10, %11, %12, %13, %14, %15, %16, %17, %18, %19, "
    "%20, %21, %22, %23, %24, %25, %26, %27, %28, %29, %30, %31, %32, %33, %34, %35, %36, %37, %38, %39, "
    "%40, %41, %42, %43, %44, %45, %46, %47, %48, %49, %50, %51, %52, %53, %54, %55, %56, %57, %58, %59, "
    "%60, %61, %62, %63}, "
    "da, db, 1, 1, 1, %74, 0;\n"
    "wgmma.commit_group.sync.aligned;\n"
    "@p bra LDA;\nmov.u32 n, 0;\nLWA:\nmbarrier.try_wait.parity.shared::cta.b64 p, [%66], %67;\n@p bra LDA;\n"
    "add.u32 n, n, 1;\nsetp.lt.u32 p, n, 0x4000;\n@p bra LWA;\nLDA:\n"
    "}"
    : "+f"(d[0]), "+f"(d[1]), "+f"(d[2]), "+f"(d[3]), "+f"(d[4]), "+f"(d[5]), "+f"(d[6]), "+f"(d[7]),
      "+f"(d[8]), "+f"(d[9]), "+f"(d[10]), "+f"(d[11]), "+f"(d[12]), "+f"(d[13]), "+f"(d[14]), "+f"(d[15]),
      "+f"(d[16]), "+f"(d[17]), "+f"(d[18]), "+f"(d[19]), "+f"(d[20]), "+f"(d[21]), "+f"(d[22]), "+f"(d[23]),
      "+f"(d[24]), "+f"(d[25]), "+f"(d[26]), "+f"(d[27]), "+f"(d[28]), "+f"(d[29]), "+f"(d[30]), "+f"(d[31]),
      "+f"(d[32]), "+f"(d[33]), "+f"(d[34]), "+f"(d[35]), "+f"(d[36]), "+f"(d[37]), "+f"(d[38]), "+f"(d[39]),
      "+f"(d[40]), "+f"(d[41]), "+f"(d[42]), "+f"(d[43]), "+f"(d[44]), "+f"(d[45]), "+f"(d[46]), "+f"(d[47]),
      "+f"(d[48]), "+f"(d[49]), "+f"(d[50]), "+f"(d[51]), "+f"(d[52]), "+f"(d[53]), "+f"(d[54]), "+f"(d[55]),
      "+f"(d[56]), "+f"(d[57]), "+f"(d[58]), "+f"(d[59]), "+f"(d[60]), "+f"(d[61]), "+f"(d[62]), "+f"(d[63])
    : "r"(alo), "r"(blo), "r"(nbar), "r"(npar), "r"(r1), "r"(c1), "r"(r2), "r"(c2), "r"(xb0), "r"(xb1),
      "n"(TA), "n"(AHI), "n"(BHI), "n"(A1), "n"(AH) : "memory");
}

__device__ __forceinline__ bool unit_is_b(int kind, int u) { return ((kind ? 0x21 : 0x15) >> u) & 1; }
__device__ __forceinline__ int unit_id(int kind, int j, int u) { return 4 * (((kind ? 0x454211 : 0x33200) >> (4 * u)) & 15) + j; }
__device__ __forceinline__ int unit_owner(int kind, int u) { return ((kind ? 0x210102 : 0x20102) >> (4 * u)) & 15; }

__device__ __forceinline__ void epoch_arrive(const Params& p, uint32_t ep) {
  uint32_t z;
  asm volatile("and.b32 %0, %1, 0;" : "=r"(z) : "r"(ep));
  const uint32_t old = atomicInc(&g_started + z, p.nblocks - 1);
  if (old == (uint32_t)p.nblocks - 1) atomicExch(&g_epoch, ep + 1);
}

constexpr int PNS = 13;
constexpr uint32_t P_ONES = PNS * 16384, P_FULL = P_ONES + 1024, P_EMPTY = P_FULL + 8 * PNS, P_EPOCH = P_EMPTY + 8 * PNS;
__device__ __forceinline__ void prep_item(int s, int i, int& type, int& row) {
  if (i < 2) { type = 1 + i; row = 64 * s; }
  else if (i == 5 || i >= 9) { type = 1 + (s & 1); row = 64 * (s >> 1) + (i == 5 ? 256 : i == 9 ? 384 : 512); }
  else { type = 0; row = 64 * s + 256 * (i < 5 ? i - 2 : i - 3); }
}
template <int TA>
__device__ __forceinline__ void prep_sum(float (&a0)[4], float (&a1)[4], uint32_t sb, int n, bool rel) {
  constexpr uint32_t ones = dlo(P_ONES, 16);
#pragma unroll 1
  for (int st = 0; st < 5; st++, n++) {
    const int lap = n / PNS, slot = n - lap * PNS;
    mbar_wait(sb + P_FULL + 8 * slot, lap & 1);
    const uint32_t a = dlo(0, 16) + slot * 1024;
    wg_fence();
#pragma unroll
    for (int kk = 0; kk < 8; kk += 2) {
      wgmma_n8<TA, 0, dhi(1024, 1), dhi(1024, 1)>(a0, a + (TA ? kk * 128 : (kk >> 2) * 512 + (kk & 3) * 2), ones, st || kk);
      wgmma_n8<TA, 0, dhi(1024, 1), dhi(1024, 1)>(a1, a + (TA ? kk * 128 + 128 : (kk >> 2) * 512 + (kk & 3) * 2 + 2), ones, st || kk);
    }
    wg_commit();
    wg_wait<0>();
    if (rel) mbar_arrive(sb + P_EMPTY + 8 * slot);
  }
  fence_regs(a0);
  fence_regs(a1);
}
__device__ __forceinline__ void lam_coef(cf& lam, cf& coef, float lre, float lim, float ldt) {
  const float dt = bf_round(expf(ldt));
  const float mag = expf(dt * lre);
  float sn, cs;
  sincospif(dt * lim * 0.31830988618379067154f, &sn, &cs);
  const float inv = 2.f / (lre * lre + lim * lim);
  const float nr = mag * cs - 1.f, ni = mag * sn;
  coef = {(nr * lre + ni * lim) * inv, (ni * lre - nr * lim) * inv};
  lam = {mag * cs, -ni};
}

__device__ __forceinline__ void prep_cta(const Params& p, uint32_t sb, int s, int warp, int lane, int tsm) {
  if (warp == 12) {
    nb_sync(2, 416);
    if (elect_one()) {
      int slot = 0, ph = 1;
#pragma unroll 1
      for (int i = 0; i < 11; i++) {
        int type, row;
        prep_item(s, i, type, row);
        const CUtensorMap* mp = &p.mp[type];
#pragma unroll 1
        for (int st = 0; st < 5; st++) {
          const uint32_t full = sb + P_FULL + 8 * slot, dst = sb + slot * 16384;
          mbar_wait(full + 8 * PNS, ph);
          mbar_expect_tx(full, 16384);
          if (type == 0) tma_2d(dst, mp, row, st * 128, full);
          else tma_3d(dst, mp, 0, row, 2 * st, full);
          if (++slot == PNS) { slot = 0; ph ^= 1; }
        }
      }
    }
  } else if (warp < 12) {
    if (elect_one()) {
      mbar_init(sb + P_FULL + 8 * warp, 1);
      mbar_init(sb + P_EMPTY + 8 * warp, 1);
      if (warp == 0) { mbar_init(sb + P_FULL + 96, 1); mbar_init(sb + P_EMPTY + 96, 1); }
      asm volatile("fence.mbarrier_init.release.cluster;" ::: "memory");
    }
    __syncwarp();
    nb_arrive(2, 416);
    if (warp == 0) {
#pragma unroll
      for (int i = 0; i < 8; i++) sts32u(sb + P_ONES + (i * 32 + lane) * 4, 0x3F803F80u);
      asm volatile("fence.proxy.async.shared::cta;" ::: "memory");
    }
    cf lam, coef;
    const int ch = 160 * s + (int)threadIdx.x - 128;
    if (warp >= 4 && warp < 9) lam_coef(lam, coef, __bfloat162float(p.lam_re[ch]), __bfloat162float(p.lam_im[ch]), __bfloat162float(p.log_dt[ch]));
    nb_sync(1, 416);
    const uint32_t tag = 1 + lds32u(sb + P_EPOCH) % 3;
    if (warp >= 4 && warp < 9) st_packet(&g_lam[ch], __float_as_uint(lam.r), __float_as_uint(lam.i), __float_as_uint(coef.r), tagw(coef.i, tag));
    const int w = warp & 3;
#pragma unroll 1
    for (int i = warp >> 2; i < 11; i += 3) {
      int type, row;
      prep_item(s, i, type, row);
      float a0[4], a1[4];
      if (type == 0) prep_sum<1>(a0, a1, sb, 5 * i, w == 0 && lane == 0);
      else           prep_sum<0>(a0, a1, sb, 5 * i, w == 0 && lane == 0);
      if ((lane & 3) == 0) {
        uint32_t* dst = &g_cs[(type == 0 ? 0 : FF + (type - 1) * DM) + row + 16 * w + (lane >> 2)];
        st_relaxed(dst, tagw(a0[0] + a1[0], tag));
        st_relaxed(dst + 8, tagw(a0[2] + a1[2], tag));
      }
      TS(1 + i);
    }
  } else if (warp == 13) {
    uint32_t ep = 0;
    if (lane == 0) {
      ep = ld_relaxed(&g_epoch);
      sts32u(sb + P_EPOCH, ep);
    }
    __syncwarp();
    nb_arrive(1, 416);
    if (lane == 0) epoch_arrive(p, ep);
    if (lane == 0) {
      int it = 0;
      while (ld_relaxed(&g_epoch) == ep && ++it < (1 << 17)) {}
    }
  }
}

__device__ __forceinline__ void producer1(const Params& p, uint32_t sb, int chunk, int kind, int j, uint32_t rank, int tsm) {
  const int NU = 5 + kind;
  if (elect_one()) {
    uint32_t slot = 0, ph = 0;
    const uint32_t wb = sb + W_OFF + rank * 2048, wf = sb + W_OFF + rank * 8192;
    const CUtensorMap* mbp = &p.mb[rank];
#pragma unroll 1
    for (int u = 0; u < NU; u++) {
      const int id = unit_id(kind, j, u);
      if (u == NU - 1) mbar_arrive(sb + B_P2GO);
      if (unit_is_b(kind, u)) {
#pragma unroll 1
        for (int kb = u ? 0 : 8; kb < 10; kb += 2) {
          const uint32_t full = sb + B_WFULL + 8 * slot, dst = wb + slot * WSLOT;
          mbar_wait(full, ph);
          mbar_expect_tx(full, WSLOT);
          mbar_wait(full + (B_WEMPTY - B_WFULL), ph);
#pragma unroll
          for (int i = 0; i < 4; i++) tma_3d_mc(dst + i * 4096, mbp, 0, 32 * id + 8 * i, kb, full);
          slot = (slot + 1) & 3;
          ph ^= (slot == 0);
        }
      } else {
#pragma unroll 1
        for (int kc = 0; kc < 640; kc += 128) {
          const uint32_t full = sb + B_WFULL + 8 * slot;
          mbar_wait(full, ph);
          mbar_expect_tx(full, WSLOT);
          mbar_wait(full + (B_WEMPTY - B_WFULL), ph);
          tma_2d_mc(wf + slot * WSLOT, &p.mw1, 64 * id, kc + rank * 64, full);
          slot = (slot + 1) & 3;
          ph ^= (slot == 0);
        }
      }
    }
  }
  __syncwarp();
  TS(1);
}

__device__ __forceinline__ void producer2(const Params& p, uint32_t sb, int chunk, int kind, int j, uint32_t rank, int lane, int tsm) {
  const int NK = kind ? 20 : 24;
  uint32_t ep = 0;
  if (lane == 0) {
    ep = ld_relaxed(&g_epoch);
    sts32u(sb + EPOCH_VAL, ep);
    mbar_arrive(sb + B_EPOCH);
    epoch_arrive(p, ep);
  }
  const uint32_t flagval = __shfl_sync(0xffffffffu, ep, 0) + 1;
  const uint32_t* flags = &g_flags[chunk][kind ? 24 : 0];
  const uint4* act = &g_act[chunk][kind ? 24 : 0][0];
  const CUtensorMap* mb = kind ? &p.mc[rank] : &p.mw2;
  uint32_t ready = 0;
  int s = 0, ph = 0;
  nb_sync(NB_WG0 + 2, 160);
  if (lane == 0) st_release(&g_flags[chunk][unit_id(kind, j, 0) + 24], flagval);
  __syncwarp();
  mbar_wait(sb + B_P2GO, 0);
  {
    const uint32_t v = lane < NK ? ld_acquire(flags + lane) : 0;
    ready = __ballot_sync(0xffffffffu, v == flagval);
    asm volatile("fence.proxy.async.global;" ::: "memory");
  }
#pragma unroll 1
  for (int kb = 0; kb < NK; kb++) {
    const uint32_t full = sb + B_FULL2 + 8 * s, st = sb + s * ST2;
    if (!((ready >> kb) & 1)) ready |= lds_acquire(sb + RDY_MASK);
    const bool known = (ready >> kb) & 1;
    mbar_wait(sb + B_EMPTY2 + 8 * s, ph);
    if (elect_one()) {
      mbar_expect_tx(full, ST2);
      const uint32_t dst = st + 16384 + rank * 10240;
      if (kind == 0) tma_3d_mc(dst, mb, 0, 64 * kb + rank * 32, 5 * j, full);
      else           tma_2d_mc(dst, mb, 32 * kb, 160 * j, full);
      if (known) bulk_load(st, act + kb * 1024, 16384, full);
    }
    __syncwarp();
    if (!known) {
      int it = 0;
      do { ready |= lds_acquire(sb + RDY_MASK); } while (!((ready >> kb) & 1) && ++it < (1 << 20));
      if (elect_one()) bulk_load(st, act + kb * 1024, 16384, full);
      __syncwarp();
    }
    if (++s == NS2) { s = 0; ph ^= 1; }
  }
  mbar_wait(sb + B_EMPTY2 + 8 * s, ph);
  if (elect_one()) {
    mbar_expect_tx(sb + B_XT, kind ? 16384 : 24576);
    for (int i = 0; i < 3 - kind; i++)
      asm volatile("cp.async.bulk.tensor.4d.shared::cluster.global.mbarrier::complete_tx::bytes [%0], [%1, {%3, %4, %5, %4}], [%2];"
                   ::"r"(sb + s * ST2 + i * 8192), "l"(&p.mx2), "r"(sb + B_XT), "r"(160 * j + 96 * kind + 32 * i), "r"(0), "r"(4 * chunk) : "memory");
  }
  __syncwarp();
}

__device__ __forceinline__ void lds4(float* d, uint32_t a) { const float4 v = lds128f(a); d[0] = v.x; d[1] = v.y; d[2] = v.z; d[3] = v.w; }

template <int MODE>
__device__ __forceinline__ void unit_mainloop(float (&acc)[64], uint32_t& c0, uint32_t& c1v, const uint32_t* csp, int csd, uint32_t sb, int u, int NU,
                                              int wg, int w, int lane, int tsm, int ui) {
  constexpr int TA = MODE == 0;
  constexpr uint32_t AHI = dhi(TA ? 1024 : 2048, 1), BHI = dhi(1024, 1), A1 = TA ? 128 : 2, AH = TA ? 512 : 64;
  const bool last = (u == NU - 1);
  const uint32_t c1 = lane < 2 && w == 0, c2 = lane < 2 && w == 1 && last;
  const uint32_t rel = mapa(sb + B_WEMPTY, lane & 1), e2 = mapa(sb + B_EMPTY2, lane & 1);
  const int nxt = NB_TURN0 + unit_owner(NU - 5, u + 1);
  uint32_t s8 = (u & 3) * 8, par = ((5 * u) >> 2) & 1;
  if (MODE == 1) {
    asm volatile("cp.async.wait_group 0;\nfence.proxy.async.shared::cta;" ::: "memory");
    nb_sync(NB_MEAN0 + 2, 128);
  } else mbar_wait(sb + B_WFULL + s8, par);
  uint32_t a = dlo(W_OFF, 16) + s8 * 128;
#pragma unroll
  for (int h = 0; h < 2; h++) {
    if (MODE == 1) mbar_wait(sb + B_XFULL + 8 * h, 0);
    if (h == 0) TS2(u, 1);
    wg_fence();
#pragma unroll
    for (int kk = 0; kk < 4; kk++) wgmma_n128<TA, 0, AHI, BHI>(acc, a + kk * A1 + h * AH, dlo(h * XKB, 16) + kk * 2, (h | kk) != 0);
    wg_commit();
  }
  TS2(u, 2);
  uint32_t o1 = s8;
  s8 = (s8 + 8) & 31;
  par ^= (s8 == 0);
  mbar_wait(sb + B_WFULL + s8, par);
  if (MODE == 1) mbar_wait(sb + B_XFULL + 16, 0);
  TS2(u, 3);
  a = dlo(W_OFF, 16) + s8 * 128;
  uint32_t n8 = (s8 + 8) & 31;
  par ^= (n8 == 0);
#pragma unroll 1
  for (uint32_t k8 = 8; k8 < 40; k8 += 8) {
    const uint32_t b = dlo(0, 16) + k8 * 256;
    if (k8 == 32 && !last) nb_arrive(nxt, 256);
    if (MODE == 0) stage_plain<TA, AHI, BHI, A1, AH>(acc, a, b, sb + B_WFULL + n8, par, rel + o1, c1, 0, 0, 0, 0);
    if (MODE == 1) stage_first<TA, AHI, BHI, A1, AH>(acc, a, b, sb + B_WFULL + n8, par, rel + o1, c1, 0, 0, sb + B_XFULL + 2 * k8 + 8, sb + B_XFULL + min(2 * k8 + 16, 72u));
    if (MODE == 2) stage_xfree<TA, AHI, BHI, A1, AH>(acc, a, b, sb + B_WFULL + n8, par, rel + o1, c1, e2 + k8 - 16, k8 > 8 ? c2 : 0, 0, 0);
    o1 = (o1 + 8) & 31;
    a = dlo(W_OFF, 16) + n8 * 128;
    if (k8 < 24) { n8 = (n8 + 8) & 31; par ^= (n8 == 0); }
    asm volatile("" : "+r"(a), "+r"(o1), "+r"(n8), "+r"(par));
  }
  TS(2 + 3 * ui);
  c0 = ld_relaxed(csp); c1v = ld_relaxed(csp + csd);
  if (MODE == 2) {
    wg_wait<1>();
    mbar_arrive_if(e2 + 24, c2);
  }
  wg_wait<0>();
  mbar_arrive_if(rel + o1, c1);
  if (w == 1 && u >= NU - 2) {
#pragma unroll
    for (int s = 0; s < NS2; s++) mbar_arrive_if(e2 + 8 * s, lane < 2 && (s >= 4 || !last));
  }
}

__device__ __forceinline__ void mean_step(float (&acc)[64], uint32_t sb, float cs0, float cs1, int q, int wg) {
  const uint32_t hi = pack_bf(cs0, cs1);
  const float f0 = cs0 - bf_lo(hi), f1 = cs1 - bf_hi(hi);
  const uint32_t mid = pack_bf(f0, f1);
  const uint32_t lo = pack_bf(f0 - bf_lo(mid), f1 - bf_hi(mid));
  const uint32_t a0 = q == 0 ? __byte_perm(hi, mid, 0x5410) : q == 1 ? (lo & 0xFFFFu) : 0u;
  const uint32_t a1 = q == 0 ? __byte_perm(hi, mid, 0x7632) : q == 1 ? (lo >> 16) : 0u;
  asm volatile("" ::"r"(a0), "r"(a1));
  nb_sync(NB_MEAN0 + wg, 128);
  wg_fence();
  wgmma_rs_n128<dhi(128, 0)>(acc, a0, a1, dlo(STAT_M, 0));
  wg_commit();
}

__device__ __forceinline__ void scan_step1(float& vr, float& vi, cf& h, float r, cf c, cf l) {
  asm volatile("{\n.reg .pred p;\n.reg .f32 t0, t1, nli, nci, ncr;\n.reg .b32 hb;\n"
               "mov.b32 hb, %2;\nsetp.ne.u32 p, hb, 0x7FC12345;\n"
               "neg.f32 nli, %8;\nneg.f32 nci, %6;\nneg.f32 ncr, %5;\n"
               "@p mul.f32 %0, %0, %4;\n@p mul.f32 %1, %1, %4;\n"
               "mul.f32 t0, %5, %0;\nmul.f32 t1, ncr, %1;\n"
               "fma.rn.f32 t0, nci, %1, t0;\nfma.rn.f32 %1, nci, %0, t1;\nmov.f32 %0, t0;\n"
               "fma.rn.f32 t0, nli, %3, %0;\nfma.rn.f32 t1, %8, %2, %1;\n"
               "fma.rn.f32 %2, %7, %2, t0;\nfma.rn.f32 %3, %7, %3, t1;\n}"
               : "+f"(vr), "+f"(vi), "+f"(h.r), "+f"(h.i) : "f"(r), "f"(c.r), "f"(c.i), "f"(l.r), "f"(l.i));
}

__device__ __forceinline__ void store_h1(const float (&acc)[64], uint4* tile, int w, int g, int q) {
  const int kr = 16 * w + g;
#pragma unroll
  for (int ii = 0; ii < 4; ii++) {
    uint32_t o0[4], o1[4];
#pragma unroll
    for (int e = 0; e < 4; e++) {
      const int i = 8 * ii + 2 * e, a = 4 * (i & 15) + (i >> 4);
      o0[e] = pack_bf_relu(acc[a], acc[a + 4]);
      o1[e] = pack_bf_relu(acc[a + 2], acc[a + 6]);
    }
    const int c16 = (q ^ (g >> 1)) + ii * 256;
    if (!(ABL & 1) || o0[0] == 0x12345) tile[c16 + kr * 4] = make_uint4(o0[0], o0[1], o0[2], o0[3]);
    if (PACE_NS > 1) __nanosleep(PACE_NS);
    if (!(ABL & 1) || o1[0] == 0x12345) tile[c16 + (kr + 8) * 4] = make_uint4(o1[0], o1[1], o1[2], o1[3]);
    if (PACE_NS && ii < 3) __nanosleep(PACE_NS);
  }
}

template <int KIND>
__device__ __forceinline__ void phase2(const Params& p, uint32_t sb, int chunk, int j, int wg, int w, int lane, uint32_t tbit, int tsm) {
  constexpr int NK = KIND ? 20 : 24;
  const int g = lane >> 2, q = lane & 3;
  const int tid = wg * 128 + w * 32 + lane;
  constexpr uint32_t AH = dhi(512, 2), BH = dhi(512, 2);
  constexpr uint32_t BLBO = KIND ? 16 : 2048;
  constexpr int TB = KIND ? 0 : 1;
  constexpr uint32_t HI_OFF = (KIND ? 96 * 64 : 3 * 2048) >> 4, KSTEP = (KIND ? 32 : 1024) >> 4;
  const uint32_t a0 = dlo(0, 4096) + wg * 512;
  constexpr uint32_t b0 = dlo(16384, BLBO);
  constexpr int NJ = KIND ? 8 : 12, J0 = KIND ? 12 : 0, NPS = KIND ? 6 : 4, NPR = KIND ? 4 : 6;
  const int t0 = 64 * (w & 1) + 8 * (2 * wg + (w >> 1)) + g;
  const uint32_t so = ((t0 >> 5) * 36 + (t0 & 31)) * 4;
  const float r0 = lds32f(sb + STAT_R + so), r1 = lds32f(sb + STAT_R + so + 144);
  const uint32_t mo = sb + STAT_M + (8 * (t0 & 15) + (t0 >> 4)) * 16;
  const uint32_t nm0 = lds32u(mo), nm1 = lds32u(mo + 32);
  uint32_t dv[NJ];
#pragma unroll
  for (int i = 0; i < NJ; i++) dv[i] = ldg_nc(p.dskip + 160 * j + 8 * J0 + 2 * q + 8 * i);
  float acc[80];
  const uint32_t e2 = mapa(sb + B_EMPTY2, lane & 1);
  uint32_t mask = (lane < 2 && w == 0) ? (2u << (NK - NS2)) - 1 : 0u;
  mbar_wait(sb + B_FULL2, 0);
  wg_fence();
#pragma unroll
  for (int kk = 0; kk < 4; kk++) wgmma_n160<1, TB, AH, BH>(acc, a0 + kk * 64, b0 + (kk >> 1) * 640 + (kk & 1) * KSTEP, kk != 0);
  wg_commit();
  TS(12);
  mbar_wait(sb + B_FULL2 + 8, 0);
  uint32_t s = 2, ph = 0, sp = 0;
  uint32_t a = a0 + (ST2 >> 4), b = b0 + (ST2 >> 4), re = e2, nb = sb + B_FULL2 + 16;
#pragma unroll 1
  for (int kb = 1; kb < NK - DTAIL; kb++) {
    kblock_n160<1, TB, AH, BH, 64, KSTEP, 640>(acc, a, b, nb, ph, re, mask & 1, 0, 0, 0);
    mask >>= 1;
    a = a0 + s * (ST2 >> 4);
    b = b0 + s * (ST2 >> 4);
    if (++sp == NS2) sp = 0;
    re = e2 + 8 * sp;
    if (++s == NS2) { s = 0; ph ^= 1; }
    nb = sb + B_FULL2 + 8 * s;
    asm volatile("" : "+r"(a), "+r"(b), "+r"(re), "+r"(nb), "+r"(ph));
  }
  constexpr int S0 = (NK - DTAIL) % NS2;
  wg_wait<0>();
  fence_regs(acc);
  if (DTAIL == 5) mbar_arrive_if(re, mask & 1);
  TS(13);
  if (tid == 0) mbar_arrive(sb + B_TAILGO);
  float lo[48], hi[32];
#pragma unroll
  for (int i = 0; i < 48; i++) asm volatile("mov.b32 %0, %1;" : "=f"(lo[i]) : "f"(acc[i]));
#pragma unroll
  for (int i = 0; i < 32; i++) asm volatile("mov.b32 %0, %1;" : "=f"(hi[i]) : "f"(acc[48 + i]));
  auto tail_full = [&](int d) { mbar_wait(sb + B_FULL2 + 8 * ((S0 + d) % NS2), ((NK - DTAIL + d) / NS2) & 1); };
  if (wg == 1) {
#pragma unroll
    for (int d = 1; d < DTAIL; d++) tail_full(d);
    nb_sync(NB_TAIL0, 256);
  }
#pragma unroll
  for (int d = 0; d < DTAIL; d++) {
    const uint32_t off = ((S0 + d) % NS2) * (ST2 >> 4);
    if (d > 0 && wg == 0) tail_full(d);
    if (d == DTAIL - 1) nb_arrive(NB_TAIL0 + wg, 256);
    wg_fence();
#pragma unroll
    for (int kk = 0; kk < 4; kk++) {
      const uint32_t bb = b0 + off + (kk >> 1) * 640 + (kk & 1) * KSTEP;
      if (!KIND) wgmma_n64<1, TB, AH, BH>(hi, a0 + off + kk * 64, bb + HI_OFF, 1);
      else       wgmma_n96<1, TB, AH, BH>(lo, a0 + off + kk * 64, bb, 1);
    }
  }
  wg_commit();
  TS(26);
  wg_wait<0>();
  if (KIND) fence_regs(lo); else fence_regs(hi);
  TS(27);
  const float hr0 = 0.5f * r0, hr1 = 0.5f * r1;
  {
    uint4* dst = KIND ? &g_xy[chunk][j][0][tid] : &g_xg[chunk][j][0][tid];
#pragma unroll
    for (int i = 0; i < NPS; i++) {
      const int c = 8 * i;
      if (KIND) st_packet(dst + i * 256, (pack_bf(lo[c], lo[c + 1]) & ~1u) | tbit, pack_bf(lo[c + 2], lo[c + 3]), pack_bf(lo[c + 4], lo[c + 5]), pack_bf(lo[c + 6], lo[c + 7]));
      else      st_packet(dst + i * 256, (pack_bf(hi[c] * hr0, hi[c + 1] * hr0) & ~1u) | tbit, pack_bf(hi[c + 2] * hr1, hi[c + 3] * hr1),
                          pack_bf(hi[c + 4] * hr0, hi[c + 5] * hr0), pack_bf(hi[c + 6] * hr1, hi[c + 7] * hr1));
    }
  }
  TS(14);
  const uint4* src = KIND ? &g_xg[chunk][j][0][tid] : &g_xy[chunk][j][0][tid];
  uint4 rv[NPR];
  auto fetch = [&]() {
#pragma unroll
    for (int i = 0; i < NPR; i++) rv[i] = ld_packet(src + i * 256);
  };
  bool got = false;
  auto try_fetch = [&]() { got = mbar_test(sb + B_RX + 8 * wg, 0); if (got) fetch(); };
  auto verify = [&]() {
    if (!got) mbar_wait(sb + B_RX + 8 * wg, 0);
    for (int it = 0; it < (1 << 14); it++) {
      if (got) {
        uint32_t bad = 0;
#pragma unroll
        for (int i = 0; i < NPR; i++) bad |= rv[i].x ^ tbit;
        if (!__any_sync(0xffffffffu, bad & 1u)) break;
      }
      fetch();
      got = true;
    }
  };
  uint32_t xv[2][NJ], xd[2][NJ];
  {
    mbar_wait(sb + B_XT, 0);
    const int row = wg * 64 + (2 * (w & 1) + ((lane >> 3) & 1)) * 16 + 8 * (w >> 1) + (lane & 7);
    const uint32_t xa = sb + ((NK - NS2) % NS2) * ST2 + row * 64;
#pragma unroll
    for (int i = 0; i < NJ; i += 2)
      asm volatile("ldmatrix.sync.aligned.m8n8.x4.shared.b16 {%0,%1,%2,%3}, [%4];"
                   : "=r"(xv[0][i]), "=r"(xv[1][i]), "=r"(xv[0][i + 1]), "=r"(xv[1][i + 1])
                   : "r"(xa + (i >> 2) * 8192 + ((((i & 3) + (lane >> 4)) ^ ((lane >> 1) & 3)) << 4)) : "memory");
  }
  auto skip_term = [&]() {
    const uint32_t rb0 = pack_bf(r0, r0), rb1 = pack_bf(r1, r1);
#pragma unroll
    for (int i = 0; i < NJ; i++) {
      xd[0][i] = bf_mul2(bf_mul2(bf_add2(xv[0][i], nm0), rb0), dv[i]);
      xd[1][i] = bf_mul2(bf_mul2(bf_add2(xv[1][i], nm1), rb1), dv[i]);
      asm volatile("" : "+r"(xd[0][i]), "+r"(xd[1][i]));
    }
  };
  if (wg == 1) skip_term();
  nb_sync(NB_TAIL0 + 1 + wg, 256);
  if (KIND) try_fetch();
  wg_fence();
#pragma unroll
  for (int d = 0; d < DTAIL; d++) {
    const uint32_t off = ((S0 + d) % NS2) * (ST2 >> 4);
    if (d == DTAIL - 1 && wg == 0) nb_arrive(NB_TAIL0 + 2, 256);
#pragma unroll
    for (int kk = 0; kk < 4; kk++) {
      const uint32_t bb = b0 + off + (kk >> 1) * 640 + (kk & 1) * KSTEP;
      if (!KIND) wgmma_n96<1, TB, AH, BH>(lo, a0 + off + kk * 64, bb, 1);
      else       wgmma_n64<1, TB, AH, BH>(hi, a0 + off + kk * 64, bb + HI_OFF, 1);
    }
  }
  wg_commit();
  if (wg == 0) skip_term();
  const uint32_t stg = sb + wg * 8192 + (32 * (w & 1) + 8 * (w >> 1) + g) * 128 + (q & 1) * 8;
  auto stage = [&](int i, float v0, float v1, float v2, float v3) {
    const uint32_t d = stg + ((S0 + (i >> 2)) % NS2) * ST2 + (((2 * (i & 3) + (q >> 1)) ^ g) << 4);
    asm volatile("st.shared.v2.f32 [%0], {%1, %2};" ::"r"(d), "f"(v0), "f"(v1) : "memory");
    asm volatile("st.shared.v2.f32 [%0], {%1, %2};" ::"r"(d + 2048), "f"(v2), "f"(v3) : "memory");
  };
  if (KIND) {
    verify();
    TS(15);
    float gt[NJ][4], tt[NJ][4];
#pragma unroll
    for (int i = 0; i < NJ; i++) {
      const uint32_t u0 = (i & 1) ? rv[i >> 1].z : rv[i >> 1].x, u1 = (i & 1) ? rv[i >> 1].w : rv[i >> 1].y;
      gt[i][0] = silu_half(bf_lo(u0)); gt[i][1] = silu_half(bf_hi(u0));
      gt[i][2] = silu_half(bf_lo(u1)); gt[i][3] = silu_half(bf_hi(u1));
      tt[i][0] = fmaf(bf_lo(xd[0][i]), gt[i][0], bf_lo(xv[0][i])); tt[i][1] = fmaf(bf_hi(xd[0][i]), gt[i][1], bf_hi(xv[0][i]));
      tt[i][2] = fmaf(bf_lo(xd[1][i]), gt[i][2], bf_lo(xv[1][i])); tt[i][3] = fmaf(bf_hi(xd[1][i]), gt[i][3], bf_hi(xv[1][i]));
    }
    wg_wait<0>();
    fence_regs(hi);
    TS(16);
#pragma unroll
    for (int i = 0; i < NJ; i++)
      stage(i, fmaf(hi[4 * i], gt[i][0], tt[i][0]), fmaf(hi[4 * i + 1], gt[i][1], tt[i][1]),
               fmaf(hi[4 * i + 2], gt[i][2], tt[i][2]), fmaf(hi[4 * i + 3], gt[i][3], tt[i][3]));
  } else {
    try_fetch();
    wg_wait<0>();
    fence_regs(lo);
    TS(16);
#pragma unroll
    for (int i = 0; i < NJ; i++) {
      lo[4 * i] = silu_half(lo[4 * i] * hr0); lo[4 * i + 1] = silu_half(lo[4 * i + 1] * hr0);
      lo[4 * i + 2] = silu_half(lo[4 * i + 2] * hr1); lo[4 * i + 3] = silu_half(lo[4 * i + 3] * hr1);
    }
    verify();
    TS(15);
#pragma unroll
    for (int i = 0; i < NJ; i++) {
      const uint32_t u0 = (i & 1) ? rv[i >> 1].z : rv[i >> 1].x, u1 = (i & 1) ? rv[i >> 1].w : rv[i >> 1].y;
      const uint32_t s0 = bf_add2(u0, xd[0][i]), s1 = bf_add2(u1, xd[1][i]);
      stage(i, fmaf(bf_lo(s0), lo[4 * i], bf_lo(xv[0][i])), fmaf(bf_hi(s0), lo[4 * i + 1], bf_hi(xv[0][i])),
               fmaf(bf_lo(s1), lo[4 * i + 2], bf_lo(xv[1][i])), fmaf(bf_hi(s1), lo[4 * i + 3], bf_hi(xv[1][i])));
    }
  }
  asm volatile("fence.proxy.async.shared::cta;" ::: "memory");
  nb_sync(NB_MEAN0 + wg, 128);
  if (w == 0 && elect_one()) {
#pragma unroll
    for (int i = 0; i < NJ / 4; i++)
      asm volatile("cp.async.bulk.tensor.4d.global.shared::cta.bulk_group [%0, {%2, %3, %4, %5}], [%1];"
                   ::"l"(&p.mo), "r"(sb + ((S0 + i) % NS2) * ST2 + wg * 8192), "r"(160 * j + 8 * J0 + 32 * i), "r"(0), "r"(wg), "r"(4 * chunk) : "memory");
    asm volatile("cp.async.bulk.commit_group;\ncp.async.bulk.wait_group.read 0;" ::: "memory");
  }
  TS(17);
}

__device__ __forceinline__ void consumer(const Params& p, uint32_t sb, int chunk, int kind, int j, int wg, int w, int lane, int tsm) {
  const int NU = 5 + kind;
  const int g = lane >> 2, q = lane & 3;
  uint32_t tag = 0;

  if (wg == 1) {
    const int n = w * 32 + lane, idx = 4 * kind + j;
    float s0 = 0.f, s1 = 0.f, q0 = 0.f, q1 = 0.f, piv = 0.f;
#pragma unroll 1
    for (int i = 0; i < 10; i++) {
      mbar_wait(sb + B_XFULL + 8 * i, 0);
      const uint4 v = lds128u(sb + i * XKB + (8 * (n >> 3) + idx) * 128 + (((n & 7) ^ idx) << 4));
      if (i == 0) piv = __shfl_sync(0xffffffffu, bf_lo(v.x), lane & 24);
      const uint32_t wv[4] = {v.x, v.y, v.z, v.w};
#pragma unroll
      for (int c = 0; c < 4; c++) {
        const float a = bf_lo(wv[c]) - piv, b = bf_hi(wv[c]) - piv;
        s0 += a; s1 += b; q0 = fmaf(a, a, q0); q1 = fmaf(b, b, q1);
      }
    }
    s0 += s1; q0 += q1;
#pragma unroll
    for (int o = 1; o < 8; o <<= 1) { s0 += __shfl_xor_sync(0xffffffffu, s0, o); q0 += __shfl_xor_sync(0xffffffffu, q0, o); }
    const float md = s0 * (1.f / DM), mean = piv + md;
    const float var = fmaxf(fmaf(-md, md, q0 * (1.f / DM)), 0.f);
    const float den = bf_round(sqrtf(bf_round(bf_round(var) + 1e-5f)));
    mbar_wait(sb + B_EPOCH, 0);
    tag = 1 + lds32u(sb + EPOCH_VAL) % 3;
    if ((lane & 7) == 0) st_relaxed2(&g_stat[chunk * 128 + idx * 16 + (n >> 3)], tagw(bf_round(mean), tag), tagw(1.f / den, tag));
    TS(18);
  }

  float acc[64];
  uint32_t c0 = 0, c1 = 0;
  if (wg == 2) unit_mainloop<1>(acc, c0, c1, &g_cs[FF + 32 * (4 * kind + j) + 8 * w + g], DM, sb, 0, NU, wg, w, lane, tsm, 0);
  int ui = 0;
#pragma unroll 1
  for (int uu = (wg + 1) % 3; uu < NU - (wg != 2); uu += (wg == 2 ? NU - 1 : 2), ui++) {
    const int u = __shfl_sync(0xffffffffu, uu, 0);
    const bool isb = unit_is_b(kind, u);
    const int id = unit_id(kind, j, u);
    const uint32_t* csp = isb ? &g_cs[FF + 32 * id + 8 * w + g] : &g_cs[64 * id + 16 * w + g];
    const int csd = isb ? DM : 8;
    if (u == 2) {
      const int n = w * 32 + lane;
      uint2 v;
      int it = 0;
      do { v = ld_relaxed2(&g_stat[chunk * 128 + n]); } while ((((v.x ^ tag) | (v.y ^ tag)) & 3u) && ++it < (1 << 17));
      const uint32_t nm = (v.x >> 16) ^ 0x8000u;
      asm volatile("st.shared.v4.u32 [%0], {%1, %2, %3, %3};" ::"r"(sb + STAT_M + (8 * (n & 15) + (n >> 4)) * 16), "r"(nm | (nm << 16)), "r"(nm), "r"(0) : "memory");
      sts32u(sb + STAT_R + ((n >> 5) * 36 + (n & 31)) * 4, v.y & ~3u);
      asm volatile("fence.proxy.async.shared::cta;" ::: "memory");
      mbar_arrive(sb + B_STATS);
      TS(1);
    }
    if (u > 0) nb_sync(NB_TURN0 + wg, 256);
    TS2(u, 0);
    if (u > 0) {
      if (isb) unit_mainloop<2>(acc, c0, c1, csp, csd, sb, u, NU, wg, w, lane, tsm, ui);
      else     unit_mainloop<0>(acc, c0, c1, csp, csd, sb, u, NU, wg, w, lane, tsm, ui);
    }
    fence_regs(acc);
    TS(3 + 3 * ui);
    TS2(u, 4);
    if (u < 2) {
      mbar_wait(sb + B_EPOCH, 0);
      tag = 1 + lds32u(sb + EPOCH_VAL) % 3;
    }
    {
      int it = 0;
      while (__any_sync(0xffffffffu, ((c0 ^ tag) | (c1 ^ tag)) & 3u) && ++it < (1 << 17)) { c0 = ld_relaxed(csp); c1 = ld_relaxed(csp + csd); }
    }
    if (ui == 0) mbar_wait(sb + B_STATS, 0);
    if (!(ABL & 8)) mean_step(acc, sb, __uint_as_float(c0 & ~3u), __uint_as_float(c1 & ~3u), q, wg);
    TS2(u, 5);
    float rt[32];
    uint4 lc = make_uint4(0, 0, 0, tag);
    if (isb) {
      lc = ld_packet(&g_lam[32 * id + 8 * w + g]);
#pragma unroll
      for (int i = 0; i < 8; i++) lds4(&rt[4 * i], sb + STAT_R + q * 144 + i * 16);
    }
    wg_wait<0>();
    fence_regs(acc);
    TS2(u, 6);
    const int kb2 = id + (isb ? 24 : 0);
    uint4* tile = &g_act[chunk][kb2][0];
    if (!isb) {
      store_h1(acc, tile, w, g, q);
    } else {
      {
        int it = 0;
        while (__any_sync(0xffffffffu, (lc.w ^ tag) & 3u) && ++it < (1 << 14)) lc = ld_packet(&g_lam[32 * id + 8 * w + g]);
      }
      const cf lam = {__uint_as_float(lc.x), __uint_as_float(lc.y)}, coef = {__uint_as_float(lc.z), __uint_as_float(lc.w & ~3u)};
      uint2* aggp = &g_agg[4 * id + w][0][g];
      cf h = {0.f, 0.f};
#pragma unroll
      for (int i = 0; i < 32; i++) {
        const int a = 4 * (i & 15) + (i >> 4);
        const float vr = acc[a] * rt[i], vi = acc[a + 2] * rt[i];
        acc[a] = fmaf(-coef.i, vi, coef.r * vr);
        acc[a + 2] = fmaf(-coef.i, vr, -coef.r * vi);
      }
      fence_regs(acc);
      __syncwarp();
#pragma unroll
      for (int i = 0; i < 32; i++) {
        const int a = 4 * (i & 15) + (i >> 4);
        h = cfma(lam, h, {acc[a], acc[a + 2]});
      }
      const cf l32 = csq(csq(csq(csq(csq(lam))))), l64 = csq(l32);
      {
        cf t = {__shfl_up_sync(0xffffffffu, h.r, 1, 4), __shfl_up_sync(0xffffffffu, h.i, 1, 4)};
        if (q >= 1) h = cfma(l32, t, h);
        t = {__shfl_up_sync(0xffffffffu, h.r, 2, 4), __shfl_up_sync(0xffffffffu, h.i, 2, 4)};
        if (q >= 2) h = cfma(l64, t, h);
      }
      if (q == 3) st_relaxed2(aggp + 8 * chunk, tagw(h.r, tag), tagw(h.i, tag));
      TS(19 + ui);
      cf ex = {__shfl_up_sync(0xffffffffu, h.r, 1, 4), __shfl_up_sync(0xffffffffu, h.i, 1, 4)};
      if (q == 0) ex = {0.f, 0.f};
      cf hin = {0.f, 0.f};
      {
        const cf l128 = csq(l64), l256 = csq(l128), l512 = csq(l256);
        uint2 v[4];
        int it = 0;
        if (POLL_NS) __nanosleep(POLL_NS);
        bool bad;
        do {
          bad = false;
#pragma unroll
          for (int m = 0; m < 4; m++) {
            const int c = chunk - 1 - q - 4 * m;
            v[m] = make_uint2(tag, tag);
            if (c >= 0 && !(ABL & 4)) v[m] = ld_relaxed2(aggp + 8 * c);
            bad |= (((v[m].x ^ tag) | (v[m].y ^ tag)) & 3u) != 0;
          }
        } while (__any_sync(0xffffffffu, bad) && ++it < (1 << 17));
#pragma unroll
        for (int m = 3; m >= 0; m--) hin = cfma(l512, hin, {__uint_as_float(v[m].x & ~3u), __uint_as_float(v[m].y & ~3u)});
        if (q & 1) hin = cmul(hin, l128);
        if (q & 2) hin = cmul(hin, l256);
        hin.r += __shfl_xor_sync(0xffffffffu, hin.r, 1); hin.i += __shfl_xor_sync(0xffffffffu, hin.i, 1);
        hin.r += __shfl_xor_sync(0xffffffffu, hin.r, 2); hin.i += __shfl_xor_sync(0xffffffffu, hin.i, 2);
        if (q & 1) hin = cmul(hin, l32);
        if (q & 2) hin = cmul(hin, l64);
      }
      TS(22 + ui);
      h = {ex.r + hin.r, ex.i + hin.i};
      const int kr = 8 * w + g;
#pragma unroll
      for (int ii = 0; ii < 4; ii++) {
        uint32_t o0[4], o1[4];
#pragma unroll
        for (int e = 0; e < 4; e++) {
          const int i = 8 * ii + 2 * e, a = 4 * (i & 15) + (i >> 4);
          cf h0 = cfma(lam, h, {acc[a], acc[a + 2]});
          h = cfma(lam, h0, {acc[a + 4], acc[a + 6]});
          if (ABL & 2) { h0 = {acc[a], acc[a + 2]}; h = {acc[a + 4], acc[a + 6]}; }
          o0[e] = pack_bf(h0.r, h.r);
          o1[e] = pack_bf(h0.i, h.i);
        }
        const int c16 = (q ^ (g >> 1)) + ii * 256;
        if (!(ABL & 1) || o0[0] == 0x12345) tile[c16 + kr * 4] = make_uint4(o0[0], o0[1], o0[2], o0[3]);
        if (!(ABL & 1) || o1[0] == 0x12345) tile[c16 + (kr + 32) * 4] = make_uint4(o1[0], o1[1], o1[2], o1[3]);
      }
    }
    if (u < NU - 1) nb_arrive(NB_WG0 + wg, 160);
    else {
      nb_sync(NB_WG0 + 3, 128);
      if (w == 0 && lane == 0) st_release(&g_flags[chunk][kb2], lds32u(sb + EPOCH_VAL) + 1);
      __syncwarp();
    }
    TS(4 + 3 * ui);
  }
  if (wg == 2) return;
  const uint32_t tbit = (lds32u(sb + EPOCH_VAL) + 1) & 1;
  if (kind) phase2<1>(p, sb, chunk, j, wg, w, lane, tbit, tsm);
  else      phase2<0>(p, sb, chunk, j, wg, w, lane, tbit, tsm);
}

__global__ void __cluster_dims__(2, 1, 1) __launch_bounds__(NTHREADS, 1) s5_ffn_fused_kernel(const __grid_constant__ Params p) {
  extern __shared__ __align__(1024) uint8_t smem_raw[];
  const uint32_t sb = __shfl_sync(0xffffffffu, smem_u32(smem_raw), 0);
  if ((sb & 0xFFFFFFu) != SB_LO) return;
  const int warp = __shfl_sync(0xffffffffu, threadIdx.x >> 5, 0), lane = threadIdx.x & 31;
  uint32_t rank, smid;
  asm volatile("mov.u32 %0, %%cluster_ctarank;" : "=r"(rank));
  asm volatile("mov.u32 %0, %%smid;" : "=r"(smid));
  const int tsm = smid;
  TS(0);
  int grp, idx;
  if (p.use_smid) {
    const int t = smid >> 1;
    if (t < 32) { grp = t & 7; idx = t >> 3; }
    else if (t < 60) { grp = 1 + (t - 32) % 7; idx = 4 + (t - 32) / 7; }
    else if (t < 62) { grp = t - 60; idx = 8; }
    else { grp = 0; idx = t - 58; }
  } else {
    const int t = blockIdx.x >> 1;
    if (t < 64) { grp = t >> 3; idx = t & 7; } else { grp = t - 64; idx = 8; }
  }
  if (idx == 8) {
    prep_cta(p, sb, 2 * grp + rank, warp, lane, tsm);
    return;
  }
  const int chunk = 2 * grp + rank, kind = idx >> 2, j = idx & 3;

  const int id0 = 4 * kind + j;
  const __nv_bfloat16* xsrc = p.x;
  uint32_t xdst = sb;
  auto cp16 = [](uint32_t d, const void* g) { asm volatile("cp.async.cg.shared.global [%0], [%1], 16;" ::"r"(d), "l"(g) : "memory"); };
  auto cp_x = [&](int kb) {
#pragma unroll
    for (int i = 0; i < 8; i++) cp16(xdst + kb * XKB + i * 2048, xsrc + kb * 64 + i * 2 * DM);
    asm volatile("cp.async.commit_group;" ::: "memory");
  };
  if (warp >= 12) {
    if (elect_one()) {
      if (warp == 12) {
        mbar_init(sb + B_XFULL + 8, 1);
        asm volatile("fence.mbarrier_init.release.cluster;" ::: "memory");
        mbar_expect_tx(sb + B_XFULL + 8, XKB);
        tma_3d(sb + XKB, &p.mx, 64, 8 * chunk, 0, sb + B_XFULL + 8);
        prefetch_map(&p.mb[rank]);
#pragma unroll
        for (int b = 10; b < 14; b++) mbar_init(sb + MISC + 8 * b, 1);
      } else if (warp == 13) {
#pragma unroll
        for (int b = 0; b < 10; b++) if (b != 1) mbar_init(sb + MISC + 8 * b, (b & 1) ? 1 : 4);
      } else if (warp == 14) {
#pragma unroll
        for (int b = 14; b < 26; b++) mbar_init(sb + MISC + 8 * b, b < 22 ? 1 : 2);
      } else {
#pragma unroll
        for (int b = 26; b < 37; b++) mbar_init(sb + MISC + 8 * b, b == 32 ? 128 : b < 35 ? 4 : 1);
        sts32u(sb + RDY_MASK, 0);
      }
      asm volatile("fence.mbarrier_init.release.cluster;" ::: "memory");
    }
    __syncwarp();
  }
  TS(24);
  asm volatile("barrier.cluster.arrive.relaxed.aligned;" ::: "memory");
  if (warp < 4) {
    const int t = threadIdx.x, n = t >> 3;
    xsrc += (size_t)(chunk * 128 + 16 * (n & 7) + (n >> 3)) * DM + (t & 7) * 8;
    xdst += n * 128 + (((t & 7) ^ (n & 7)) << 4);
    cp_x(0);
  } else if (warp >= 8 && warp < 12) {
    const int t = threadIdx.x & 127, row = (t >> 3) & 7;
    const size_t off = (size_t)(32 * id0 + row) * DM + (t >> 6) * 64 + (t & 7) * 8;
    const uint32_t d = sb + W_OFF + (t >> 6) * 1024 + row * 128 + (((t & 7) ^ row) << 4);
#pragma unroll
    for (int m = 0; m < 8; m++) cp16(d + m * 2048, ((m & 1) ? p.b_im : p.b_re) + off + (m >> 1) * 8 * DM);
    asm volatile("cp.async.commit_group;" ::: "memory");
  }
  if (warp == 14 && elect_one()) {
    prefetch_map(&p.mw1);
    prefetch_map(kind ? &p.mc[rank] : &p.mw2);
    prefetch_map(&p.mo);
    prefetch_map(&p.mx2);
  }
  if (warp < 4) cp_x(2);
  asm volatile("barrier.cluster.wait.acquire.aligned;" ::: "memory");
  TS(25);
  if (warp >= 12) {
    asm volatile("setmaxnreg.dec.sync.aligned.u32 32;");
    if (warp == 12 && elect_one()) {
      mbar_arrive(sb + B_WFULL);
#pragma unroll
      for (int st = 1; st < 4; st++) {
        mbar_expect_tx(sb + B_WFULL + 8 * st, WSLOT);
#pragma unroll
        for (int i = 0; i < 4; i++) tma_3d_mc(sb + W_OFF + st * WSLOT + rank * 2048 + i * 4096, &p.mb[rank], 0, 32 * id0 + 8 * i, 2 * st, sb + B_WFULL + 8 * st);
#pragma unroll
        for (int kb = 2 * st + 1; kb < (st == 3 ? 10 : 2 * st + 2); kb += 2) {
          mbar_expect_tx(sb + B_XFULL + 8 * kb, XKB);
          tma_3d(sb + kb * XKB, &p.mx, kb * 64, 8 * chunk, 0, sb + B_XFULL + 8 * kb);
        }
      }
    }
    __syncwarp();

    if (warp == 12) producer1(p, sb, chunk, kind, j, rank, tsm);
    else if (warp == 13) producer2(p, sb, chunk, kind, j, rank, lane, tsm);
    else {
      if (warp == 15) {
        const int cta = chunk * 8 + idx;
        const char* w1p = reinterpret_cast<const char*>(p.w1) + (cta * 5 + (lane >> 3)) * (FF * 2) + (lane & 7) * 128;
        mbar_wait(sb + B_XFULL + 8 * PF_AT, 0);
#pragma unroll 1
        for (int c = 0; c < (PF_MODE == 1 ? 1 : PF_MODE == 2 ? 0 : 3); c++) {
          asm volatile("prefetch.global.L2 [%0];" ::"l"(w1p + c * 1024) : "memory");
          if (lane < 8) asm volatile("prefetch.global.L2 [%0];" ::"l"(w1p + c * 1024 + 4 * FF * 2) : "memory");
          if (c == 0) mbar_wait(sb + B_XFULL + 72, 0);
          else __nanosleep(PF_NS);
          if (c == 1) {
            l2_prefetch(reinterpret_cast<const char*>((cta & 1) ? p.b_im : p.b_re) + 256 * DM * 2 + (cta >> 1) * 7680, 60, lane);
            __nanosleep(PF_NS);
          }
        }
        if (PF_MODE) __nanosleep(3000);
        l2_prefetch(reinterpret_cast<const char*>(p.w2) + cta * 7680, 60, lane);
        __nanosleep(PF_NS);
        l2_prefetch(reinterpret_cast<const char*>(p.w2) + (128 + cta) * 7680, 60, lane);
        __nanosleep(PF_NS);
        l2_prefetch(reinterpret_cast<const char*>(p.c_re) + cta * 6400, 50, lane);
        __nanosleep(PF_NS);
        l2_prefetch(reinterpret_cast<const char*>(p.c_im) + cta * 6400, 50, lane);
      }
      mbar_wait(sb + B_EPOCH, 0);
      const uint32_t flagval = lds32u(sb + EPOCH_VAL) + 1;
#pragma unroll 1
      for (int u = warp - 13; u < 4 + kind; u += 2) {
        nb_sync(NB_WG0 + warp - 14, 160);
        if (lane == 0) st_release(&g_flags[chunk][unit_id(kind, j, u) + (unit_is_b(kind, u) ? 24 : 0)], flagval);
        __syncwarp();
      }
      if (warp == 14) {
        const int NK = kind ? 20 : 24;
        const uint32_t* flags = &g_flags[chunk][kind ? 24 : 0];
        uint32_t seen = 0;
#pragma unroll 1
        for (int it = 0; it < (1 << 14) && seen != (1u << NK) - 1; it++) {
          uint32_t r = __ballot_sync(0xffffffffu, lane < NK && ld_relaxed(flags + lane) == flagval);
          if (r != seen) {
            r = __ballot_sync(0xffffffffu, lane < NK && ld_acquire(flags + lane) == flagval);
            asm volatile("fence.proxy.async.global;" ::: "memory");
            __syncwarp();
            if (lane == 0) asm volatile("st.release.cta.shared.u32 [%0], %1;" ::"r"(sb + RDY_MASK), "r"(r) : "memory");
            seen = r;
          } else __nanosleep(100);
        }
      }
      mbar_wait(sb + B_TAILGO, 0);
      if (lane < 4) {
        const uint4* src = (kind ? &g_xg[chunk][j][3][0] : &g_xy[chunk][j][5][0]) + (warp - 14) * 128 + lane * 32;
        int it = 0;
        while (((ld_relaxed(&src->x) ^ flagval) & 1u) && ++it < (1 << 14)) {}
        mbar_arrive(sb + B_RX + 8 * (warp - 14));
      }
    }
  } else {
    if (warp < 4) {
#define XDONE(n, kb) asm volatile("cp.async.wait_group " #n ";\nfence.proxy.async.shared::cta;" ::: "memory"); __syncwarp(); if (lane == 0) mbar_arrive(sb + B_XFULL + 8 * kb);
      cp_x(4); XDONE(2, 0) cp_x(6); XDONE(2, 2) cp_x(8); XDONE(2, 4) XDONE(1, 6) XDONE(0, 8)
#undef XDONE
    }
    asm volatile("setmaxnreg.inc.sync.aligned.u32 160;");
    consumer(p, sb, chunk, kind, j, warp >> 2, warp & 3, lane, tsm);
  }
}

typedef CUresult (*EncodeFn)(CUtensorMap*, CUtensorMapDataType, cuuint32_t, void*, const cuuint64_t*, const cuuint64_t*, const cuuint32_t*,
                             const cuuint32_t*, CUtensorMapInterleave, CUtensorMapSwizzle, CUtensorMapL2promotion, CUtensorMapFloatOOBfill);

void make_map(EncodeFn fn, CUtensorMap* m, const void* ptr, int rank, const cuuint64_t* dims, const cuuint64_t* strides, const cuuint32_t* box,
              CUtensorMapSwizzle swz, CUtensorMapDataType dt = CU_TENSOR_MAP_DATA_TYPE_BFLOAT16) {
  const cuuint32_t es[5] = {1, 1, 1, 1, 1};
  CUresult r = fn(m, dt, rank, const_cast<void*>(ptr), dims, strides, box, es, CU_TENSOR_MAP_INTERLEAVE_NONE, swz,
                  CU_TENSOR_MAP_L2_PROMOTION_L2_128B, CU_TENSOR_MAP_FLOAT_OOB_FILL_NONE);
  (void)r;
}

}

extern "C" void kernel_launch(void* const* d_in, const int* in_sizes, int n_in, void* d_out, int out_size) {
  (void)in_sizes; (void)n_in; (void)out_size;
  static EncodeFn encode = nullptr;
  static int sms = 0;
  if (!encode) {
    void* fn = nullptr;
    cudaDriverEntryPointQueryResult qr;
    cudaGetDriverEntryPoint("cuTensorMapEncodeTiled", &fn, cudaEnableDefault, &qr);
    encode = (EncodeFn)fn;
    int dev = 0;
    cudaGetDevice(&dev);
    cudaDeviceGetAttribute(&sms, cudaDevAttrMultiProcessorCount, dev);
    cudaFuncSetAttribute(s5_ffn_fused_kernel, cudaFuncAttributeMaxDynamicSharedMemorySize, SMEM_BYTES);
  }
  Params p;
  {
    const cuuint64_t d[3] = {DM, SEQ / 16, 16}, st[2] = {16 * DM * 2, DM * 2};
    const cuuint32_t b[3] = {64, 8, 16};
    make_map(encode, &p.mx, d_in[0], 3, d, st, b, CU_TENSOR_MAP_SWIZZLE_128B);
  }
  for (int i = 0; i < 2; i++) {
    const cuuint64_t d[2] = {DM, DM}, st[1] = {DM * 2};
    const cuuint32_t b[3] = {64, 8, 2}, c[2] = {32, 160};
    const cuuint64_t dp[3] = {64, DM, 10}, sp[2] = {DM * 2, 128};
    const cuuint32_t bp[3] = {64, 64, 2};
    make_map(encode, &p.mb[i], d_in[3 + i], 3, dp, sp, b, CU_TENSOR_MAP_SWIZZLE_128B);
    make_map(encode, &p.mp[1 + i], d_in[3 + i], 3, dp, sp, bp, CU_TENSOR_MAP_SWIZZLE_128B);
    make_map(encode, &p.mc[i], d_in[5 + i], 2, d, st, c, CU_TENSOR_MAP_SWIZZLE_64B);
  }
  {
    const cuuint64_t d[2] = {FF, DM}, st[1] = {FF * 2};
    const cuuint32_t b[2] = {64, 64}, bp[2] = {64, 128};
    make_map(encode, &p.mw1, d_in[10], 2, d, st, b, CU_TENSOR_MAP_SWIZZLE_128B);
    make_map(encode, &p.mp[0], d_in[10], 2, d, st, bp, CU_TENSOR_MAP_SWIZZLE_128B);
  }
  {
    const cuuint64_t d[3] = {32, FF, DM / 32}, st[2] = {DM * 2, 64};
    const cuuint32_t b[3] = {32, 32, 5};
    make_map(encode, &p.mw2, d_in[11], 3, d, st, b, CU_TENSOR_MAP_SWIZZLE_64B);
  }
  {
    const cuuint64_t d[4] = {DM, 16, SEQ / 32, 2}, st[3] = {DM * 2, 32 * DM * 2, 16 * DM * 2};
    const cuuint32_t b[4] = {32, 16, 4, 2};
    make_map(encode, &p.mx2, d_in[0], 4, d, st, b, CU_TENSOR_MAP_SWIZZLE_64B);
  }
  {
    const cuuint64_t d[4] = {DM, 16, 2, SEQ / 32}, st[3] = {DM * 4, 16 * DM * 4, 32 * DM * 4};
    const cuuint32_t b[4] = {32, 16, 1, 4};
    make_map(encode, &p.mo, d_out, 4, d, st, b, CU_TENSOR_MAP_SWIZZLE_128B, CU_TENSOR_MAP_DATA_TYPE_FLOAT32);
  }
  p.x = (const __nv_bfloat16*)d_in[0];
  p.lam_re = (const __nv_bfloat16*)d_in[1];
  p.lam_im = (const __nv_bfloat16*)d_in[2];
  p.log_dt = (const __nv_bfloat16*)d_in[7];
  p.dskip = (const __nv_bfloat16*)d_in[8];
  p.b_re = (const __nv_bfloat16*)d_in[3];
  p.b_im = (const __nv_bfloat16*)d_in[4];
  p.w1 = (const __nv_bfloat16*)d_in[10];
  p.c_re = (const __nv_bfloat16*)d_in[5];
  p.c_im = (const __nv_bfloat16*)d_in[6];
  p.w2 = (const __nv_bfloat16*)d_in[11];
  p.out = (float*)d_out;
  p.use_smid = (sms == 132);
  p.nblocks = 132;
  s5_ffn_fused_kernel<<<p.nblocks, NTHREADS, SMEM_BYTES>>>(p);
}
```
